```python
import torch

def _softmax(x, axis=-1):
    return torch.softmax(x, dim=axis)
def _gelu(x):
    return torch.nn.functional.gelu(x, approximate="tanh")
def _silu(x):
    return torch.nn.functional.silu(x)
def _sigmoid(x):
    return torch.sigmoid(x)
def _layernorm(x, axis=-1, eps=1e-5):
    m = x.mean(dim=axis, keepdim=True)
    v = x.var(dim=axis, keepdim=True, unbiased=False)
    return (x - m) / torch.sqrt(v + eps)
def _scatter_add(tgt, idx, src, axis=0):
    return tgt.clone().index_add_(axis, idx, src)
def _segment_sum(src, seg, n):
    out = torch.zeros((n,) + src.shape[1:], dtype=src.dtype)
    return out.index_add_(0, seg, src)
def _pad(x, pw):
    flat = tuple(v for pair in reversed(pw) for v in pair)
    return torch.nn.functional.pad(x, flat)

kernel_name = 'recurrent_scan__linear_attn_block__glu_gated_swiglu__prompt'

def setup_inputs():

    _w = (lambda a: (lambda t: t.to(torch.bfloat16) if t.is_floating_point() else t)(torch.as_tensor(a)))
    def _A_setup():
        B, S, D = 1, 2048, 640
        return {
            "x": _w((lambda *s: torch.randn(*s, dtype=torch.bfloat16) * 0.05)(B, S, D)),
            "wqkv": _w((lambda *s: torch.randn(*s, dtype=torch.bfloat16) * 0.8)(D, 3 * D)),
            "wo": _w((lambda *s: torch.randn(*s, dtype=torch.bfloat16) * 0.8)(D, D)),
        }
    _A_in = _A_setup()

    def _B_setup():
        B, S, D, F = 1, 2048, 640, 1728
        return {
            "x": _w((lambda *s: torch.randn(*s, dtype=torch.bfloat16) * 0.05)(B, S, D)),
            "w1": _w((lambda *s: torch.randn(*s, dtype=torch.bfloat16) * 0.2)(D, F) * (2.0 / D) ** 0.5),
            "w3": _w((lambda *s: torch.randn(*s, dtype=torch.bfloat16) * 0.2)(D, F) * (2.0 / D) ** 0.5),
            "w2": _w((lambda *s: torch.randn(*s, dtype=torch.bfloat16) * 0.2)(F, D) * (2.0 / F) ** 0.5),
        }
    _B_in = _B_setup()

    return {
        "A_x": _A_in["x"],
        "A_wqkv": _A_in["wqkv"],
        "A_wo": _A_in["wo"],
        "B_x": _B_in["x"],
        "B_w1": _B_in["w1"],
        "B_w3": _B_in["w3"],
        "B_w2": _B_in["w2"],
    }

def reference(A_x, A_wqkv, A_wo, B_x, B_w1, B_w3, B_w2):
    def _A_ref(x, wqkv, wo):
        B, S, D = x.shape
        H = 32; Dh = D // H
        qkv = (lambda x, *d: x.permute(*d))((x @ wqkv).reshape(B, S, 3, H, Dh), 2, 0, 3, 1, 4)
        q, k, v = qkv[0], qkv[1], qkv[2]
        phi = lambda t: torch.where(t > 0, t + 1, torch.exp(t)) + 1e-6
        pq, pk = phi(q), phi(k)
        kv = torch.einsum("bhsd,bhse->bhde", pk, v)
        z = torch.einsum("bhsd->bhd", pk)
        num = torch.einsum("bhqd,bhde->bhqe", pq, kv)
        den = torch.einsum("bhqd,bhd->bhq", pq, z)[..., None] + 1e-6
        o = num / den
        return (lambda x, *d: x.permute(*d))(o, 0, 2, 1, 3).reshape(B, S, D) @ wo

    def _B_ref(x, w1, w3, w2):
        gate = torch.einsum("bsd,df->bsf", x, w1)
        up = torch.einsum("bsd,df->bsf", x, w3)
        h = _silu(gate) * up
        out = torch.einsum("bsf,fd->bsd", h, w2)
        return out

    x = A_x
    xn = _layernorm(x, axis=-1)
    s = _A_ref(xn, A_wqkv, A_wo)
    g = _silu(_B_ref(xn, B_w1, B_w3, B_w2))
    return x + s * g
```

```cpp
#include <cuda_runtime.h>
#include <cuda_bf16.h>
#include <cuda.h>
#include <stdint.h>
#include <stdio.h>
#include <math.h>

namespace {

constexpr int S_ = 2048, D_ = 640, F_ = 1728;
constexpr int TB = 94;
constexpr int NRB = 22;
constexpr int NCTA = 132;
constexpr int KTP = NRB * 96;
constexpr int NKVC = 121;
constexpr int NMC = 110;
constexpr int NS1 = 5;
constexpr int NS2 = 7;
constexpr uint32_t ST2 = 26624;
constexpr int NK2 = 37;

constexpr uint32_t XOFF = 0;
constexpr uint32_t XCH = 12288;
constexpr uint32_t WOFF = 122880;
constexpr uint32_t SOFF = 204800;
constexpr uint32_t MOFF = 229376;
constexpr uint32_t B_FULL = MOFF;
constexpr uint32_t B_EMPTY = B_FULL + 40;
constexpr uint32_t B_XFULL = B_EMPTY + 40;
constexpr uint32_t B_FULL2 = B_XFULL + 80;
constexpr uint32_t B_EMPTY2 = B_FULL2 + 56;
constexpr uint32_t B_STATS = B_EMPTY2 + 56;
constexpr uint32_t B_XRES = B_STATS + 8;
constexpr uint32_t B_STG = B_XRES + 8;
constexpr uint32_t B_STGF = B_STG + 16;
constexpr uint32_t B_KVF = B_STGF + 16;
constexpr uint32_t B_MF = B_KVF + 8;
constexpr uint32_t B_DUMMY = B_MF + 8;
constexpr uint32_t B_WO = B_DUMMY + 8;
constexpr uint32_t B_AL = B_WO + 8;
constexpr uint32_t B_Z = B_AL + 8;
constexpr uint32_t B_AD = B_Z + 8;
constexpr uint32_t W_READY = MOFF + 384;
constexpr uint32_t W_KV = MOFF + 388;
constexpr uint32_t W_B = MOFF + 392;
constexpr uint32_t W_ZERO = MOFF + 396;
constexpr uint32_t STATS = MOFF + 400;
constexpr uint32_t ZS = STATS;
constexpr uint32_t SMEM_BYTES = ZS + 2560;
constexpr uint32_t WOOFF = 133120;
static_assert(SMEM_BYTES <= 232448, "smem");

#define PLACE 1
#define XEARLY 1
#define TOKD 2
#define CH_L 2
#define CH_A 2
#define CH_F 1
#define PACE 320
#define T0_DELAY 4150

struct Sync {
  unsigned long long stats[NRB * 96];
  unsigned hflag[27 * 32];
  unsigned tslot[160];
  unsigned c_kv[32], c_q[32], c_p[32], c_b[32], c_m[32], c_done[32];
  unsigned c_a[32];
};

__device__ __align__(1024) __nv_bfloat16 g_H[S_ * F_];
__device__ __align__(1024) __nv_bfloat16 g_PQ[S_ * D_];
__device__ __align__(1024) __nv_bfloat16 g_M[D_ * D_];
__device__ __align__(1024) __nv_bfloat16 g_KVT[2 * D_ * KTP];
__device__ __align__(1024) __nv_bfloat16 g_mask[4 * KTP];
__device__ __align__(1024) __nv_bfloat16 g_B[11 * 64 * 64];
__device__ __align__(1024) float g_z[D_];
__device__ __align__(1024) float g_kvp[32 * 11 * 400];
__device__ __align__(1024) float g_zp[11 * D_];
__device__ __align__(1024) Sync g_sync;
#define STAMP(i) do {} while (0)

#define TRAP(id) __trap()

struct Params {
  CUtensorMap x1, wqkv, w1, w3, hst, pqst, w2, mm, hld, ald, xres, out, kva, kvb, vld, msk, wom, bld, mst;
  const __nv_bfloat16* wo;
  const __nv_bfloat16* w2p;
  __nv_bfloat16 *mask_p, *pq_p, *b_p;
  float *kvp, *zp, *z;
  Sync* sy;
  uint32_t zero;
};

__device__ __forceinline__ unsigned long long gtime() { unsigned long long g; asm volatile("mov.u64 %0, %%globaltimer;" : "=l"(g)::"memory"); return g; }
__device__ __forceinline__ uint32_t gtime32() { uint32_t g; asm volatile("mov.u32 %0, %%globaltimer_lo;" : "=r"(g)::"memory"); return g; }
__device__ __forceinline__ uint32_t clk32() { uint32_t c; asm volatile("mov.u32 %0, %%clock;" : "=r"(c)::"memory"); return c; }
__device__ __forceinline__ bool elect_one() { uint32_t p; asm volatile("{.reg .pred P; elect.sync _|P, 0xffffffff; selp.u32 %0,1,0,P;}" : "=r"(p)); return p; }
__device__ __forceinline__ void mbar_init(uint32_t bar, uint32_t cnt) { asm volatile("mbarrier.init.shared::cta.b64 [%0], %1;" ::"r"(bar), "r"(cnt) : "memory"); }
__device__ __forceinline__ void mbar_expect_tx(uint32_t bar, uint32_t bytes) { asm volatile("mbarrier.arrive.expect_tx.shared::cta.b64 _, [%0], %1;" ::"r"(bar), "r"(bytes) : "memory"); }
__device__ __forceinline__ void mbar_arrive(uint32_t bar) { asm volatile("mbarrier.arrive.shared::cta.b64 _, [%0];" ::"r"(bar) : "memory"); }
__device__ __forceinline__ bool mbar_test(uint32_t bar, uint32_t parity) {
  uint32_t ok;
  asm volatile("{.reg .pred p; mbarrier.test_wait.parity.shared::cta.b64 p, [%1], %2; selp.u32 %0,1,0,p;}" : "=r"(ok) : "r"(bar), "r"(parity) : "memory");
  return ok;
}
__device__ __forceinline__ bool mbar_try(uint32_t bar, uint32_t parity) {
  uint32_t ok;
  asm volatile("{.reg .pred p; mbarrier.try_wait.parity.shared::cta.b64 p, [%1], %2; selp.u32 %0,1,0,p;}" : "=r"(ok) : "r"(bar), "r"(parity) : "memory");
  return ok;
}
constexpr uint32_t SPIN_LIMIT = 1u << 22;
__device__ __forceinline__ void mbar_wait(uint32_t bar, uint32_t parity) {
  asm volatile("{\n.reg .pred p;\n.reg .u32 c;\nmov.u32 c, 0;\n"
               "LW:\nmbarrier.try_wait.parity.shared::cta.b64 p, [%0], %1;\n@p bra LD;\n"
               "add.u32 c, c, 1;\nsetp.lt.u32 p, c, %2;\n@p bra LW;\ntrap;\nLD:\n}" ::"r"(bar), "r"(parity), "n"(SPIN_LIMIT) : "memory");
}
__device__ __forceinline__ void tma_ld(uint32_t dst, const CUtensorMap* m, int c0, int c1, uint32_t bar) {
  asm volatile("cp.async.bulk.tensor.2d.shared::cluster.global.mbarrier::complete_tx::bytes [%0], [%1, {%3,%4}], [%2];"
               ::"r"(dst), "l"(m), "r"(bar), "r"(c0), "r"(c1) : "memory");
}
__device__ __forceinline__ void expect_e(uint32_t bar, uint32_t bytes) {
  asm volatile("{.reg .pred P; elect.sync _|P, 0xffffffff; @P mbarrier.arrive.expect_tx.shared::cta.b64 _, [%0], %1;}" ::"r"(bar), "r"(bytes) : "memory");
}
__device__ __forceinline__ void tma_ld_e(uint32_t dst, const CUtensorMap* m, int c0, int c1, uint32_t bar) {
  asm volatile("{.reg .pred P; elect.sync _|P, 0xffffffff;\n"
               "@P cp.async.bulk.tensor.2d.shared::cluster.global.mbarrier::complete_tx::bytes [%0], [%1, {%3,%4}], [%2];}"
               ::"r"(dst), "l"(m), "r"(bar), "r"(c0), "r"(c1) : "memory");
}
__device__ __forceinline__ void tma_st(const CUtensorMap* m, int c0, int c1, uint32_t src) {
  asm volatile("cp.async.bulk.tensor.2d.global.shared::cta.bulk_group [%0, {%2,%3}], [%1];" ::"l"(m), "r"(src), "r"(c0), "r"(c1) : "memory");
}
__device__ __forceinline__ void bulk_ld(uint32_t dst, const void* src, uint32_t bytes, uint32_t bar) {
  asm volatile("cp.async.bulk.shared::cluster.global.mbarrier::complete_tx::bytes [%0], [%1], %2, [%3];" ::"r"(dst), "l"(src), "r"(bytes), "r"(bar) : "memory");
}
__device__ __forceinline__ void bulk_st(void* dst, uint32_t src, uint32_t bytes) {
  asm volatile("cp.async.bulk.global.shared::cta.bulk_group [%0], [%1], %2;" ::"l"(dst), "r"(src), "r"(bytes) : "memory");
}
__device__ __forceinline__ void tma_pf(const CUtensorMap* m, int c0, int c1) {
  asm volatile("cp.async.bulk.prefetch.tensor.2d.L2.global.tile [%0, {%1,%2}];" ::"l"(m), "r"(c0), "r"(c1) : "memory");
}
__device__ __forceinline__ void bulk_pf(const void* p, uint32_t bytes) { asm volatile("cp.async.bulk.prefetch.L2.global [%0], %1;" ::"l"(p), "r"(bytes) : "memory"); }
__device__ __forceinline__ void desc_pf(const CUtensorMap* m) { asm volatile("prefetch.tensormap [%0];" ::"l"(m) : "memory"); }
__device__ __forceinline__ void bulk_commit() { asm volatile("cp.async.bulk.commit_group;" ::: "memory"); }
__device__ __forceinline__ void bulk_wait_read() { asm volatile("cp.async.bulk.wait_group.read 0;" ::: "memory"); }
__device__ __forceinline__ void bulk_wait_all() { asm volatile("cp.async.bulk.wait_group 0;" ::: "memory"); }
__device__ __forceinline__ void fence_async_smem() { asm volatile("fence.proxy.async.shared::cta;" ::: "memory"); }
__device__ __forceinline__ void fence_async_global() { asm volatile("fence.proxy.async.global;" ::: "memory"); }
__device__ __forceinline__ void bar_sync(int id, int n) { asm volatile("bar.sync %0, %1;" ::"r"(id), "r"(n) : "memory"); }
__device__ __forceinline__ void bar_arrive(int id, int n) { asm volatile("bar.arrive %0, %1;" ::"r"(id), "r"(n) : "memory"); }
__device__ __forceinline__ void wg_fence() { asm volatile("wgmma.fence.sync.aligned;" ::: "memory"); }
__device__ __forceinline__ void wg_commit() { asm volatile("wgmma.commit_group.sync.aligned;" ::: "memory"); }
template <int N> __device__ __forceinline__ void wg_wait() { asm volatile("wgmma.wait_group.sync.aligned %0;" ::"n"(N) : "memory"); }
template <int N> __device__ __forceinline__ void keep(float (&d)[N]) {
#pragma unroll
  for (int i = 0; i < N; i++) asm volatile("" : "+f"(d[i])::"memory");
}
__device__ __forceinline__ unsigned ld_rlx(const unsigned* p) { unsigned v; asm volatile("ld.relaxed.gpu.global.u32 %0, [%1];" : "=r"(v) : "l"(p) : "memory"); return v; }
__device__ __forceinline__ unsigned long long ld_rlx64(const unsigned long long* p) { unsigned long long v; asm volatile("ld.relaxed.gpu.global.u64 %0, [%1];" : "=l"(v) : "l"(p) : "memory"); return v; }
__device__ __forceinline__ void st_rlx(unsigned* p, unsigned v) { asm volatile("st.relaxed.gpu.global.u32 [%0], %1;" ::"l"(p), "r"(v) : "memory"); }
__device__ __forceinline__ void st_rlx64(unsigned long long* p, unsigned long long v) { asm volatile("st.relaxed.gpu.global.u64 [%0], %1;" ::"l"(p), "l"(v) : "memory"); }
__device__ __forceinline__ void fence_acq() { asm volatile("fence.acquire.gpu;" ::: "memory"); }
__device__ __forceinline__ void red_rlx(unsigned* p, unsigned v) { asm volatile("red.relaxed.gpu.global.add.u32 [%0], %1;" ::"l"(p), "r"(v) : "memory"); }
__device__ __forceinline__ void red_rel(unsigned* p, unsigned v) { asm volatile("red.release.gpu.global.add.u32 [%0], %1;" ::"l"(p), "r"(v) : "memory"); }
__device__ __forceinline__ unsigned lds_acq(uint32_t a) { unsigned v; asm volatile("ld.acquire.cta.shared::cta.u32 %0, [%1];" : "=r"(v) : "r"(a) : "memory"); return v; }
__device__ __forceinline__ void sts_rel(uint32_t a, unsigned v) { asm volatile("st.release.cta.shared::cta.u32 [%0], %1;" ::"r"(a), "r"(v) : "memory"); }
__device__ __forceinline__ unsigned long long lds64v(uint32_t a) { unsigned long long v; asm volatile("ld.volatile.shared::cta.u64 %0, [%1];" : "=l"(v) : "r"(a) : "memory"); return v; }
__device__ __forceinline__ void sts64v(uint32_t a, unsigned long long v) { asm volatile("st.volatile.shared::cta.u64 [%0], %1;" ::"r"(a), "l"(v) : "memory"); }
__device__ __forceinline__ uint4 lds128(uint32_t a) { uint4 v; asm volatile("ld.shared.v4.u32 {%0,%1,%2,%3}, [%4];" : "=r"(v.x), "=r"(v.y), "=r"(v.z), "=r"(v.w) : "r"(a) : "memory"); return v; }
__device__ __forceinline__ float4 lds128f(uint32_t a) { float4 v; asm volatile("ld.shared.v4.f32 {%0,%1,%2,%3}, [%4];" : "=f"(v.x), "=f"(v.y), "=f"(v.z), "=f"(v.w) : "r"(a) : "memory"); return v; }
__device__ __forceinline__ void sts128(uint32_t a, uint4 v) { asm volatile("st.shared.v4.u32 [%0], {%1,%2,%3,%4};" ::"r"(a), "r"(v.x), "r"(v.y), "r"(v.z), "r"(v.w) : "memory"); }
__device__ __forceinline__ void stsm4t(uint32_t a, uint32_t r0, uint32_t r1, uint32_t r2, uint32_t r3) {
  asm volatile("stmatrix.sync.aligned.m8n8.x4.trans.shared.b16 [%0], {%1,%2,%3,%4};" ::"r"(a), "r"(r0), "r"(r1), "r"(r2), "r"(r3) : "memory");
}
__device__ __forceinline__ void stsm4(uint32_t a, uint32_t r0, uint32_t r1, uint32_t r2, uint32_t r3) {
  asm volatile("stmatrix.sync.aligned.m8n8.x4.shared.b16 [%0], {%1,%2,%3,%4};" ::"r"(a), "r"(r0), "r"(r1), "r"(r2), "r"(r3) : "memory");
}
__device__ __forceinline__ void ldsm4t(uint32_t a, uint32_t& r0, uint32_t& r1, uint32_t& r2, uint32_t& r3) {
  asm volatile("ldmatrix.sync.aligned.m8n8.x4.trans.shared.b16 {%0,%1,%2,%3}, [%4];" : "=r"(r0), "=r"(r1), "=r"(r2), "=r"(r3) : "r"(a) : "memory");
}
__device__ __forceinline__ uint32_t pack2(float lo, float hi) { uint32_t r; asm("cvt.rn.bf16x2.f32 %0, %1, %2;" : "=r"(r) : "f"(hi), "f"(lo)); return r; }
__device__ __forceinline__ float bf_lo(uint32_t v) { return __uint_as_float(v << 16); }
__device__ __forceinline__ float bf_hi(uint32_t v) { return __uint_as_float(v & 0xffff0000u); }
__device__ __forceinline__ float ex2(float x) { float y; asm("ex2.approx.ftz.f32 %0, %1;" : "=f"(y) : "f"(x)); return y; }
__device__ __forceinline__ float rcp(float x) { float y; asm("rcp.approx.ftz.f32 %0, %1;" : "=f"(y) : "f"(x)); return y; }
constexpr float LOG2E = 1.4426950408889634f, LN2 = 0.6931471805599453f;
__device__ __forceinline__ float silu(float g) { return g * rcp(1.f + ex2(g * -1.4426950408889634f)); }
__device__ __forceinline__ float phi_l(float yl) { return fmaxf(fmaf(yl, LN2, 1.000001f), __saturatef(ex2(yl) + 1e-6f)); }
__host__ __device__ constexpr uint32_t dlo(uint32_t off) { return ((1024u + off) >> 4) | (1u << 16); }
__device__ __forceinline__ void arrive_elect(uint32_t bar) {
  asm volatile("{.reg .pred P; elect.sync _|P, 0xffffffff; @P mbarrier.arrive.shared::cta.b64 _, [%0];}" ::"r"(bar) : "memory");
}
__device__ __forceinline__ void wait_count(const unsigned* p, unsigned target) {
  if ((threadIdx.x & 31) == 0) {
    uint32_t c = 0;
    while (ld_rlx(p) < target) { __nanosleep(200); if (++c > SPIN_LIMIT) TRAP(target); }
    fence_acq();
  }
  __syncwarp();
}

__device__ __forceinline__ void wgmma_n96(float (&d)[48], uint32_t da, uint32_t db, int sd) {
  asm volatile("{.reg .pred p; .reg .b64 da, db; setp.ne.b32 p, %50, 0;\n"
    "mov.b64 da, {%48, 0x40000040}; mov.b64 db, {%49, 0x40000040};\n"
    "wgmma.mma_async.sync.aligned.m64n96k16.f32.bf16.bf16 "
    "{%0, %1, %2, %3, %4, %5, %6, %7, %8, %9, %10, %11, %12, %13, %14, %15, "
    "%16, %17, %18, %19, %20, %21, %22, %23, %24, %25, %26, %27, %28, %29, %30, %31, "
    "%32, %33, %34, %35, %36, %37, %38, %39, %40, %41, %42, %43, %44, %45, %46, %47}, "
    "da, db, p, 1, 1, 1, 0;}"
    : "+f"(d[0]), "+f"(d[1]), "+f"(d[2]), "+f"(d[3]), "+f"(d[4]), "+f"(d[5]), "+f"(d[6]), "+f"(d[7]),
      "+f"(d[8]), "+f"(d[9]), "+f"(d[10]), "+f"(d[11]), "+f"(d[12]), "+f"(d[13]), "+f"(d[14]), "+f"(d[15]),
      "+f"(d[16]), "+f"(d[17]), "+f"(d[18]), "+f"(d[19]), "+f"(d[20]), "+f"(d[21]), "+f"(d[22]), "+f"(d[23]),
      "+f"(d[24]), "+f"(d[25]), "+f"(d[26]), "+f"(d[27]), "+f"(d[28]), "+f"(d[29]), "+f"(d[30]), "+f"(d[31]),
      "+f"(d[32]), "+f"(d[33]), "+f"(d[34]), "+f"(d[35]), "+f"(d[36]), "+f"(d[37]), "+f"(d[38]), "+f"(d[39]),
      "+f"(d[40]), "+f"(d[41]), "+f"(d[42]), "+f"(d[43]), "+f"(d[44]), "+f"(d[45]), "+f"(d[46]), "+f"(d[47])
    : "r"(da), "r"(db), "r"(sd));
}
__device__ __forceinline__ void wgmma_n80(float (&d)[40], uint32_t da, uint32_t db, int sd) {
  asm volatile("{.reg .pred p; .reg .b64 da, db; setp.ne.b32 p, %42, 0;\n"
    "mov.b64 da, {%40, 0x40000040}; mov.b64 db, {%41, 0x40000040};\n"
    "wgmma.mma_async.sync.aligned.m64n80k16.f32.bf16.bf16 "
    "{%0, %1, %2, %3, %4, %5, %6, %7, %8, %9, %10, %11, %12, %13, %14, %15, "
    "%16, %17, %18, %19, %20, %21, %22, %23, %24, %25, %26, %27, %28, %29, %30, %31, "
    "%32, %33, %34, %35, %36, %37, %38, %39}, "
    "da, db, p, 1, 1, 1, 0;}"
    : "+f"(d[0]), "+f"(d[1]), "+f"(d[2]), "+f"(d[3]), "+f"(d[4]), "+f"(d[5]), "+f"(d[6]), "+f"(d[7]),
      "+f"(d[8]), "+f"(d[9]), "+f"(d[10]), "+f"(d[11]), "+f"(d[12]), "+f"(d[13]), "+f"(d[14]), "+f"(d[15]),
      "+f"(d[16]), "+f"(d[17]), "+f"(d[18]), "+f"(d[19]), "+f"(d[20]), "+f"(d[21]), "+f"(d[22]), "+f"(d[23]),
      "+f"(d[24]), "+f"(d[25]), "+f"(d[26]), "+f"(d[27]), "+f"(d[28]), "+f"(d[29]), "+f"(d[30]), "+f"(d[31]),
      "+f"(d[32]), "+f"(d[33]), "+f"(d[34]), "+f"(d[35]), "+f"(d[36]), "+f"(d[37]), "+f"(d[38]), "+f"(d[39])
    : "r"(da), "r"(db), "r"(sd));
}
__device__ __forceinline__ void wgmma_n64_kk(float (&d)[32], uint32_t da, uint32_t db, int sd) {
  asm volatile("{.reg .pred p; .reg .b64 da, db; setp.ne.b32 p, %34, 0;\n"
    "mov.b64 da, {%32, 0x40000040}; mov.b64 db, {%33, 0x40000040};\n"
    "wgmma.mma_async.sync.aligned.m64n64k16.f32.bf16.bf16 "
    "{%0, %1, %2, %3, %4, %5, %6, %7, %8, %9, %10, %11, %12, %13, %14, %15, "
    "%16, %17, %18, %19, %20, %21, %22, %23, %24, %25, %26, %27, %28, %29, %30, %31}, "
    "da, db, p, 1, 1, 0, 0;}"
    : "+f"(d[0]), "+f"(d[1]), "+f"(d[2]), "+f"(d[3]), "+f"(d[4]), "+f"(d[5]), "+f"(d[6]), "+f"(d[7]),
      "+f"(d[8]), "+f"(d[9]), "+f"(d[10]), "+f"(d[11]), "+f"(d[12]), "+f"(d[13]), "+f"(d[14]), "+f"(d[15]),
      "+f"(d[16]), "+f"(d[17]), "+f"(d[18]), "+f"(d[19]), "+f"(d[20]), "+f"(d[21]), "+f"(d[22]), "+f"(d[23]),
      "+f"(d[24]), "+f"(d[25]), "+f"(d[26]), "+f"(d[27]), "+f"(d[28]), "+f"(d[29]), "+f"(d[30]), "+f"(d[31])
    : "r"(da), "r"(db), "r"(sd));
}
__device__ __forceinline__ void wgmma_n64(float (&d)[32], uint32_t da, uint32_t db, int sd) {
  asm volatile("{.reg .pred p; .reg .b64 da, db; setp.ne.b32 p, %34, 0;\n"
    "mov.b64 da, {%32, 0x40000040}; mov.b64 db, {%33, 0x40000040};\n"
    "wgmma.mma_async.sync.aligned.m64n64k16.f32.bf16.bf16 "
    "{%0, %1, %2, %3, %4, %5, %6, %7, %8, %9, %10, %11, %12, %13, %14, %15, "
    "%16, %17, %18, %19, %20, %21, %22, %23, %24, %25, %26, %27, %28, %29, %30, %31}, "
    "da, db, p, 1, 1, 1, 0;}"
    : "+f"(d[0]), "+f"(d[1]), "+f"(d[2]), "+f"(d[3]), "+f"(d[4]), "+f"(d[5]), "+f"(d[6]), "+f"(d[7]),
      "+f"(d[8]), "+f"(d[9]), "+f"(d[10]), "+f"(d[11]), "+f"(d[12]), "+f"(d[13]), "+f"(d[14]), "+f"(d[15]),
      "+f"(d[16]), "+f"(d[17]), "+f"(d[18]), "+f"(d[19]), "+f"(d[20]), "+f"(d[21]), "+f"(d[22]), "+f"(d[23]),
      "+f"(d[24]), "+f"(d[25]), "+f"(d[26]), "+f"(d[27]), "+f"(d[28]), "+f"(d[29]), "+f"(d[30]), "+f"(d[31])
    : "r"(da), "r"(db), "r"(sd));
}

__device__ __forceinline__ void role1(int b, int& G, int& rb) {
  const int hi = b >= 66, c = b - 66 * hi; rb = c / 3; G = 3 * hi + (c - 3 * rb);
}
enum { T_KV = 0, T_QQ = 1, T_FFN = 2 };
__device__ __forceinline__ int step_info(int G, int s, int& i) {
  if (s < 2 && G < 5) { i = 2 * G + s; return T_KV; }
  if (s < 3 && G >= 3) { i = (G == 5) ? 4 + 2 * s : 2 * (G - 3); return T_QQ; }
  i = (s == 2) ? G : 3 + 6 * (s - 3) + G;
  return T_FFN;
}
__device__ __forceinline__ void step_src(const Params& p, int G, int s, const CUtensorMap*& m0, const CUtensorMap*& m1, int& c0, int& c1) {
  int i;
  const int ty = step_info(G, s, i);
  m0 = ty == T_FFN ? &p.w1 : &p.wqkv; m1 = ty == T_FFN ? &p.w3 : &p.wqkv;
  c0 = 64 * i + (ty == T_KV ? 640 : 0); c1 = c0 + (ty == T_KV ? 640 : (ty == T_QQ ? 64 : 0));
}

__device__ __forceinline__ uint32_t p2_stage(uint32_t slot) { return ((uint32_t)(0x94684EAE341A00ull >> (8 * slot)) & 255u) << 10; }

__device__ __forceinline__ void producer(const Params& p, uint32_t sb, int b, int lane) {
  int G, rb;
  role1(b, G, rb);
  const uint32_t gt0 = gtime32(), ck0 = clk32();
  uint32_t tmine = 0, ts[5];
  {
    const int c0 = (G == 5) ? 256 : 640 + 128 * G, c1 = c0 + (G == 5 ? 64 : 640);
#pragma unroll 1
    for (int kt = 1; kt < 10; kt++) {
      if (kt < NS1) {
        expect_e(sb + B_FULL + 8 * kt, 16384);
        tma_ld_e(sb + WOFF + kt * 16384, &p.wqkv, c0, kt * 64, sb + B_FULL + 8 * kt);
        tma_ld_e(sb + WOFF + kt * 16384 + 8192, &p.wqkv, c1, kt * 64, sb + B_FULL + 8 * kt);
      }
      expect_e(sb + B_XFULL + 8 * kt, TB * 128);
      tma_ld_e(sb + XOFF + kt * XCH, &p.x1, kt * 64, rb * TB, sb + B_XFULL + 8 * kt);
    }
    if (elect_one()) STAMP(49);
  }
#pragma unroll 1
  for (int s = 0; s < 7; s++) {
    const CUtensorMap *m0, *m1; int c0, c1;
    step_src(p, G, s, m0, m1, c0, c1);
    if (s == 4) {
      uint32_t c = 0;
      while (lds_acq(sb + W_KV) == 0) { if (++c > (SPIN_LIMIT << 4)) TRAP(0); }
      const int kcol = (b % 11) * 192, krow = min(b / 11, 10) * 60;
#pragma unroll 1
      for (int j = 0; j < 3; j++) {
        mbar_wait(sb + B_EMPTY + 8 * j, 1);
        expect_e(sb + B_FULL + 8 * j, 16384);
        tma_ld_e(sb + WOFF + j * 16384, &p.kva, kcol + 64 * j, krow, sb + B_FULL + 8 * j);
        tma_ld_e(sb + WOFF + j * 16384 + 8192, &p.vld, kcol + 64 * j, D_ + krow, sb + B_FULL + 8 * j);
        tma_ld_e(sb + WOFF + j * 16384 + 8192 + 60 * 128, &p.msk, kcol + 64 * j, 0, sb + B_FULL + 8 * j);
      }
    }
    if (s == 6) {
      const uint32_t g = __shfl_sync(0xffffffffu, gtime32(), 0);
      const float ns_per_clk = __fdividef((float)(g - gt0), (float)(clk32() - ck0));
      tmine = (g + (uint32_t)(T0_DELAY * ns_per_clk)) | 1u;
      tmine = __shfl_sync(0xffffffffu, tmine, 0);
      if (lane == 0) st_rlx(&p.sy->tslot[b], tmine);
    }
    const uint32_t rot = s >= 4;
    const uint32_t dA = sb + WOFF + rot * (3 * 16384), dB = sb + WOFF - rot * (2 * 16384);
    const uint32_t fA = sb + B_FULL + rot * 24, fB = sb + B_FULL - rot * 16;
#pragma unroll 1
    for (uint32_t h = (s == 0); h < 2; h++) {
      const int k0 = h * 320;
      if (s == 6 && h == 1) {
#pragma unroll
        for (int q = 0; q < 5; q++) ts[q] = (q * 32 + lane < NCTA) ? ld_rlx(&p.sy->tslot[q * 32 + lane]) : tmine;
      }
#pragma unroll
      for (int j = 0; j < 5; j++) {
        const uint32_t fb = (j < 2 ? fA : fB) + 8 * j, dst = (j < 2 ? dA : dB) + j * 16384;
        mbar_wait(fb + (B_EMPTY - B_FULL), (j < 2 ? h : h ^ rot) ^ 1);
        expect_e(fb, 16384);
        tma_ld_e(dst, m0, c0, k0 + j * 64, fb);
        tma_ld_e(dst + 8192, m1, c1, k0 + j * 64, fb);
      }
    }
  }
  if (elect_one()) STAMP(40);
  if (b >= 130) return;
  const int tb = b / 5, cg = b - tb * 5;
  {
    uint32_t c = 0;
    while (__any_sync(0xffffffffu, (ts[0] == 0) | (ts[1] == 0) | (ts[2] == 0) | (ts[3] == 0) | (ts[4] == 0))) {
#pragma unroll
      for (int q = 0; q < 5; q++) ts[q] = (q * 32 + lane < NCTA) ? ld_rlx(&p.sy->tslot[q * 32 + lane]) : tmine;
      if (++c > SPIN_LIMIT) TRAP(0);
    }
    int d = 0;
#pragma unroll
    for (int q = 0; q < 5; q++) d = max(d, (int)(ts[q] - tmine));
    const uint32_t T0 = tmine + __reduce_max_sync(0xffffffffu, d);
    while ((int)(gtime32() - T0) < 0) { if (++c > (SPIN_LIMIT << 4)) TRAP(0); }
  }
  if (elect_one()) STAMP(41);
  uint32_t cnext = clk32();
  uint32_t ready = 0, slot = 0, par = 1;
  const CUtensorMap *mA = &p.w2, *mB = &p.hld;
  int k0 = 0;
#pragma unroll 1
  for (int i = 0; i < NK2; i++) {
    const uint32_t dA = sb + p2_stage(slot), fb = sb + B_FULL2 + 8 * slot;
    if (i == 27) { mA = &p.mm; mB = &p.ald; k0 = 0; }
    if (i >= NS2) mbar_wait(fb + (B_EMPTY2 - B_FULL2), par);
    else if (i == 2) mbar_wait(sb + B_EMPTY + 8 * 4, 1);
    else if (i == 4) mbar_wait(sb + B_EMPTY + 8 * 1, 0);
    else if (i == 5) mbar_wait(sb + B_EMPTY + 8 * 2, 0);
    if ((uint32_t)i >= ready) {
      uint32_t c = 0;
      while ((ready = lds_acq(sb + W_READY)) <= (uint32_t)i) { if (++c > (SPIN_LIMIT << 4)) TRAP(0); }
    }
    expect_e(fb, ST2);
    while ((int)(clk32() - cnext) < 0) {}
    cnext += PACE;
    tma_ld_e(dA, mA, cg * 128, k0, fb);
    tma_ld_e(dA + 8192, mA, cg * 128 + 64, k0, fb);
    tma_ld_e(dA + 16384, mB, k0, tb * 80, fb);
    if (i == 4 && b < NMC) {
      uint32_t c = 0;
      while (lds_acq(sb + W_B) == 0) { if (++c > (SPIN_LIMIT << 4)) TRAP(0); }
      expect_e(sb + B_WO, 16384);
      tma_ld_e(sb + WOOFF, &p.wom, (b % 10) * 64, (b / 10) * 60, sb + B_WO);
      tma_ld_e(sb + WOOFF + 8192, &p.bld, 0, (b / 10) * 64, sb + B_WO);
    }
    if (i == 20) {
      mbar_wait(sb + B_STG, 1);
      if (b < 128) mbar_wait(sb + B_AD, 0);
      expect_e(sb + B_XRES, 2 * 80 * 128);
      tma_ld_e(sb + SOFF, &p.xres, cg * 128, tb * 80, sb + B_XRES);
      tma_ld_e(sb + SOFF + XCH, &p.xres, cg * 128 + 64, tb * 80, sb + B_XRES);
    }
    k0 += 64;
    if (++slot == NS2) { slot = 0; par ^= 1; }
  }
  if (elect_one()) STAMP(42);
}

__device__ __forceinline__ void agent(const Params& p, uint32_t sb, int b, int lane) {
  Sync* sy = p.sy;
  int G, rb;
  role1(b, G, rb);
  const bool ph2 = b < 130;
  const int tb = b / 5;
  const unsigned* f0; const unsigned* f1; unsigned t0v = 1, t1v = 1;
  if (lane < 27) { f0 = &sy->hflag[lane * 32 + (tb * 80) / TB]; f1 = &sy->hflag[lane * 32 + min(tb * 80 + 79, S_ - 1) / TB]; }
  else { f0 = &sy->c_m[0]; f1 = &sy->c_a[tb]; t0v = NMC; t1v = (tb == 25) ? 3 : 5; }
  bool ok = !ph2 || lane > 27, mdone = b >= NMC;
  unsigned published = 0;
  int s = 0;
  const CUtensorMap *n0, *n1; int d0, d1;
  step_src(p, G, min(lane + 1, 6), n0, n1, d0, d1);
  if (rb >= 10) { n0 = n1; d0 = d1; }
  d1 = (rb < 10 ? rb : rb - 10) * 64;
  if (rb < 20 && lane < 2) tma_pf(n0, d0, d1);
  if (lane < 19) desc_pf(&p.x1 + lane);
  uint32_t c = 0;
#pragma unroll 1
  while (true) {
    if (s < 7) {
      if (s < 4 ? mbar_try(sb + B_STGF + 8 * (s & 1), (s >> 1) & 1) : mbar_test(sb + B_STGF + 8 * (s & 1), (s >> 1) & 1)) {
        if (lane == 0) {
          int ix;
          const int ty = step_info(G, s, ix);
          if (ty == T_FFN) tma_st(&p.hst, 64 * ix, rb * TB, sb + SOFF);
          else if (ty == T_QQ) { tma_st(&p.pqst, 64 * ix, rb * TB, sb + SOFF); tma_st(&p.pqst, 64 * ix + 64, rb * TB, sb + SOFF + XCH); }
          else {
            const int ca = rb * 96 + (rb & 1) * 32, cb = rb * 96 + 64 - (rb & 1) * 64;
            tma_st(&p.kva, ca, 64 * ix, sb + SOFF); tma_st(&p.kvb, cb, 64 * ix, sb + SOFF + 8192);
            tma_st(&p.kva, ca, D_ + 64 * ix, sb + SOFF + XCH); tma_st(&p.kvb, cb, D_ + 64 * ix, sb + SOFF + XCH + 8192);
          }
          bulk_commit();
          bulk_wait_read();
          mbar_arrive(sb + B_STG + 8 * (s & 1));
          bulk_wait_all();
          red_rlx(ty == T_FFN ? &sy->hflag[ix * 32 + rb] : (ty == T_QQ ? &sy->c_q[0] : &sy->c_kv[0]), 1);
          STAMP(50 + s);
          if (s == 0 && b < 128) {
            bulk_pf(reinterpret_cast<const char*>(p.wo) + b * 6400, 6400);
            bulk_pf(reinterpret_cast<const char*>(p.w2p) + b * 17280, 17280);
          }
        }
        if (rb < 20 && lane == s + 2 && s < 4) tma_pf(n0, d0, d1);
        __syncwarp();
        s++;
      }
    } else if (!mdone) {
      if (mbar_test(sb + B_MF, 0)) {
        mdone = true;
        if (lane == 0) {
          tma_st(&p.mst, (b % 10) * 64, (b / 10) * 60, sb + WOOFF + 8192);
          bulk_commit();
          bulk_wait_all();
          red_rlx(&sy->c_m[0], 1);
          STAMP(45);
        }
        __syncwarp();
      }
    }
    if (s >= 4) {
      unsigned v0 = 0, v1 = 0;
      if (!ok) { v0 = ld_rlx(f0); v1 = ld_rlx(f1); }
      {
        const uint32_t lb = s < 7 ? sb + B_STGF + 8 * (s & 1) : sb + B_MF, lp = s < 7 ? (s >> 1) & 1 : 0, t0 = clk32();
        bool hit = false;
        if (s < 7 || !mdone) while (clk32() - t0 < 600 && !(hit = mbar_test(lb, lp))) {}
        if (hit) continue;
      }
      ok = ok || ((v0 >= t0v) & (v1 >= t1v));
      const unsigned m = __ballot_sync(0xffffffffu, ok);
      unsigned n = __ffs(~m | 0x10000000u) - 1;
      if (n == 28) n = NK2;
      if (n > published) {
        published = n;
        fence_acq();
        __syncwarp();
        if (lane == 0) { fence_async_global(); sts_rel(sb + W_READY, n); }
      }
      if (m == 0xffffffffu && s == 7 && mdone) break;
    }
    if (++c > SPIN_LIMIT) TRAP(s);
  }
  if (ph2) mbar_wait(sb + B_XRES, 0);
  bar_sync(6, 96);
  unsigned last = 0;
  if (lane == 0) { __threadfence(); last = atomicAdd(&sy->c_done[0], 1) == NCTA - 1; }
  if (__shfl_sync(0xffffffffu, last, 0)) {
    __threadfence();
    uint4* w = reinterpret_cast<uint4*>(sy);
#pragma unroll 1
    for (int i = lane; i < (int)(sizeof(Sync) / 16); i += 32) w[i] = make_uint4(0, 0, 0, 0);
  }
}

__device__ __forceinline__ void aux(const Params& p, uint32_t sb, int b, int aw, int lane) {
  Sync* sy = p.sy;
  char* rows = reinterpret_cast<char*>(p.pq_p + (size_t)16 * b * D_);
  const uint32_t abuf = sb + SOFF + XCH;
  if (b == 0) {
#pragma unroll 1
    for (int i = aw * 32 + lane; i < KTP / 8; i += 64) {
      const int rb = i / 12, q = i - 12 * rb;
      const int left = min(TB, S_ - rb * TB) - 8 * ((rb & 1) ? (q < 4 ? q + 8 : q - 4) : q);
      reinterpret_cast<uint4*>(p.mask_p)[i] =
          make_uint4(left > 0 ? 0x3F803F80u : 0u, left > 2 ? 0x3F803F80u : 0u, left > 4 ? 0x3F803F80u : 0u, left > 6 ? 0x3F803F80u : 0u);
    }
    __syncwarp();
    if (lane == 0) red_rel(&sy->c_kv[0], 1);
  }
  if (aw == 0) {
    int G, rb;
    role1(b, G, rb);
#pragma unroll 1
    for (int q = 0; q < 3; q++) {
      unsigned long long v;
      uint32_t c = 0;
      while ((v = ld_rlx64(&sy->stats[rb * 96 + q * 32 + lane])) == 0) { if (++c > SPIN_LIMIT) TRAP(0); }
      sts64v(sb + STATS + 8 * (q * 32 + lane), v);
    }
    mbar_arrive(sb + B_STATS);
    __syncwarp();
    wait_count(&sy->c_kv[0], 10 * NRB + 2);
    if (lane == 0) { fence_async_global(); sts_rel(sb + W_KV, 1); STAMP(44); }
    if (b < NKVC) {
      mbar_wait(sb + B_KVF, 0);
      if (lane == 0) red_rel(&sy->c_p[0], 1);
    }
    if (b < 128) {
      wait_count(&sy->c_p[0], NKVC);
      if (lane == 0) STAMP(43);
      const int u = 25 * b + lane, head = u / 100, r = u - 100 * head, zu = 2 * b + lane - 25;
      const bool isz = lane >= 25;
      if (lane < 25 || (lane < 27 && zu < D_ / 4)) {
        const float4* src = isz ? reinterpret_cast<const float4*>(p.zp) + zu : reinterpret_cast<const float4*>(p.kvp + head * 11 * 400) + r;
        const int stride = isz ? D_ / 4 : 100;
        float4 s = make_float4(0.f, 0.f, 0.f, 0.f);
#pragma unroll
        for (int q = 0; q < 11; q++) {
          const float4 v = __ldcg(src + q * stride);
          s.x += v.x; s.y += v.y; s.z += v.z; s.w += v.w;
        }
        if (isz) reinterpret_cast<float4*>(p.z)[zu] = s;
        else {
          const int hg = head / 3, hl = head - 3 * hg, d = r / 5;
          *reinterpret_cast<uint2*>(p.b_p + (64 * hg + 20 * hl + d) * 64 + 20 * hl + 4 * (r - 5 * d)) =
              make_uint2(pack2(s.x * LN2, s.y * LN2), pack2(s.z * LN2, s.w * LN2));
        }
      }
      __syncwarp();
      if (lane == 0) red_rel(&sy->c_b[0], 1);
    }
  } else if (b < 128) {
    wait_count(&sy->c_q[0], 5 * NRB);
    if (lane == 0) { fence_async_global(); mbar_expect_tx(sb + B_AL, 10240); bulk_ld(abuf, rows, 10240, sb + B_AL); }
  }
  if (b < 128) {
    if (aw == 1) {
      wait_count(&sy->c_b[0], 128);
      if (lane == 0) {
        fence_async_global();
        sts_rel(sb + W_B, 1);
        mbar_expect_tx(sb + B_Z, 2560);
        bulk_ld(sb + ZS, p.z, 2560, sb + B_Z);
        STAMP(46);
      }
    }
    mbar_wait(sb + B_Z, 0);
    float z[20];
#pragma unroll
    for (int i = 0; i < 5; i++) {
      const float4 t = lds128f(sb + ZS + 80 * lane + 16 * i);
      z[4 * i] = t.x; z[4 * i + 1] = t.y; z[4 * i + 2] = t.z; z[4 * i + 3] = t.w;
    }
#pragma unroll 1
    for (int r = 0; r < 2; r++) {
      mbar_wait(sb + B_AL, r);
#pragma unroll 1
      for (int tk = 0; tk < 4; tk++) {
        const uint32_t a = abuf + (4 * aw + tk) * 1280 + 40 * lane;
        uint2 v[5];
#pragma unroll
        for (int i = 0; i < 5; i++) asm volatile("ld.shared.v2.u32 {%0,%1}, [%2];" : "=r"(v[i].x), "=r"(v[i].y) : "r"(a + 8 * i) : "memory");
        float den = 1e-6f, den2 = 0.f;
#pragma unroll
        for (int i = 0; i < 5; i++) {
          den = fmaf(bf_lo(v[i].x), z[4 * i], den); den2 = fmaf(bf_hi(v[i].x), z[4 * i + 1], den2);
          den = fmaf(bf_lo(v[i].y), z[4 * i + 2], den); den2 = fmaf(bf_hi(v[i].y), z[4 * i + 3], den2);
        }
        const float inv = rcp(den + den2);
#pragma unroll
        for (int i = 0; i < 5; i++)
          asm volatile("st.shared.v2.u32 [%0], {%1,%2};" ::"r"(a + 8 * i), "r"(pack2(bf_lo(v[i].x) * inv, bf_hi(v[i].x) * inv)),
                       "r"(pack2(bf_lo(v[i].y) * inv, bf_hi(v[i].y) * inv)) : "memory");
      }
      fence_async_smem();
      bar_sync(5, 64);
      if (aw == 0 && lane == 0) {
        bulk_st(rows + r * 10240, abuf, 10240);
        bulk_commit();
        bulk_wait_all();
        if (r == 0) { mbar_expect_tx(sb + B_AL, 10240); bulk_ld(abuf, rows + 10240, 10240, sb + B_AL); }
        else { red_rlx(&sy->c_a[b / 5], 1); mbar_arrive(sb + B_AD); STAMP(47); }
      }
      __syncwarp();
    }
  }
  bar_arrive(6, 96);
}

__device__ __forceinline__ void ln_stats(uint32_t sb, int tid, int G, int rb, Sync* sy) {
  const int tok = 16 * G + (tid >> 3);
  uint32_t a = sb + XOFF + tok * 128;
  mbar_wait(sb + B_XFULL, 0);
  uint32_t p0;
  asm volatile("ld.shared.u32 %0, [%1];" : "=r"(p0) : "r"(a) : "memory");
  const float piv = bf_lo(p0);
  float sm = 0.f, sq = 0.f;
  a += (tid & 7) * 16;
#pragma unroll 1
  for (int c = 0; c < 10; c++) {
    mbar_wait(sb + B_XFULL + 8 * c, 0);
    const uint4 v = lds128(a + c * XCH);
    const uint32_t w[4] = {v.x, v.y, v.z, v.w};
#pragma unroll
    for (int q = 0; q < 4; q++) {
      const float d0 = bf_lo(w[q]) - piv, d1 = bf_hi(w[q]) - piv;
      sm += d0 + d1;
      sq = fmaf(d0, d0, fmaf(d1, d1, sq));
    }
  }
#pragma unroll
  for (int o = 1; o < 8; o <<= 1) { sm += __shfl_xor_sync(0xffffffffu, sm, o); sq += __shfl_xor_sync(0xffffffffu, sq, o); }
  if ((tid & 7) == 0) {
    const float dm = sm * (1.f / D_);
    const float var = fmaxf(sq * (1.f / D_) - dm * dm, 0.f);
    uint32_t rl = __float_as_uint(rsqrtf(var + 1e-5f) * LOG2E);
    if (tok >= min(TB, S_ - rb * TB) || rl == 0) rl = 0x80000000u;
    st_rlx64(&sy->stats[rb * 96 + tok], ((unsigned long long)rl << 32) | __float_as_uint(-(piv + dm)));
  }
}

__device__ __forceinline__ void load_stats(float (&st)[48], uint32_t sb, int lane) {
  mbar_wait(sb + B_STATS, 0);
#pragma unroll
  for (int j = 0; j < 12; j++) {
    const float4 v = lds128f(sb + STATS + 16 * (lane & 3) + 64 * j);
    st[4 * j] = v.x; st[4 * j + 1] = v.y; st[4 * j + 2] = v.z; st[4 * j + 3] = v.w;
  }
}
__device__ __forceinline__ void chain(float& v, uint32_t after, uint32_t zero) {
  v = __uint_as_float(__float_as_uint(v) | (after & zero));
}
__device__ __forceinline__ uint32_t token(uint32_t a) { uint32_t v; asm volatile("ld.volatile.shared::cta.u32 %0, [%1];" : "=r"(v) : "r"(a) : "memory"); return v; }
__device__ __forceinline__ void link(float& v, uint32_t tok) { v = __uint_as_float(__float_as_uint(v) | tok); }
template <bool PHI, bool TRANS>
__device__ __forceinline__ void epi_attn(const float (&a)[48], const float (&st)[48], int lane, uint32_t zero, uint32_t zaddr,
                                         uint32_t dst, uint32_t dst2) {
  float c0 = __shfl_sync(0xffffffffu, a[44], lane | 3), c1 = __shfl_sync(0xffffffffu, a[46], lane | 3);
  uint32_t plo = 0, phi_ = 0, tok = 0;
#pragma unroll
  for (int j = 0; j < 12; j++) {
    float y[4];
#pragma unroll
    for (int q = 0; q < 4; q++) {
      const float yl = fmaf(st[4 * j + 2 * (q & 1)], q < 2 ? c0 : c1, a[4 * j + q]) * st[4 * j + 2 * (q & 1) + 1];
      y[q] = PHI ? phi_l(yl) : yl;
    }
    const uint32_t lo = pack2(y[0], y[1]), hi = pack2(y[2], y[3]);
    if ((j + 1) % (PHI ? CH_A : CH_L) == 0 && j < 11) { chain(c0, lo, zero); chain(c1, hi, zero); }
    if (j >= 2 && j % 2 == TOKD - 1 && j < 11) link(c0, tok);
    if (j & 1) {
      if (TRANS) stsm4t(dst + (j - 1) * 1024, plo, phi_, lo, hi);
      else stsm4((j < 8 ? dst : dst2) ^ (((j - 1) & 7) << 4), plo, phi_, lo, hi);
      if (j + TOKD < 11) tok = token(zaddr);
    }
    plo = lo; phi_ = hi;
  }
}
__device__ __forceinline__ void epi_ffn(const float (&a)[48], const float (&u)[48], const float (&st)[48], int lane, uint32_t zero, uint32_t zaddr, uint32_t stg_lane) {
  float cg0 = __shfl_sync(0xffffffffu, a[44], lane | 3), cg1 = __shfl_sync(0xffffffffu, a[46], lane | 3);
  float cu0 = __shfl_sync(0xffffffffu, u[44], lane | 3), cu1 = __shfl_sync(0xffffffffu, u[46], lane | 3);
  uint32_t plo = 0, phi_ = 0, tok = 0;
#pragma unroll
  for (int j = 0; j < 12; j++) {
    float h[4];
#pragma unroll
    for (int q = 0; q < 4; q++) {
      const float nm = st[4 * j + 2 * (q & 1)], rl = st[4 * j + 2 * (q & 1) + 1];
      const float gl = fmaf(nm, q < 2 ? cg0 : cg1, a[4 * j + q]) * rl;
      const float du = fmaf(nm, q < 2 ? cu0 : cu1, u[4 * j + q]);
      h[q] = (gl * du) * (rl * rcp(fmaf(ex2(-gl), LOG2E * LOG2E, LOG2E * LOG2E)));
    }
    const uint32_t lo = pack2(h[0], h[1]), hi = pack2(h[2], h[3]);
    if ((j & 1) == 0 && j >= 2 && j < 11) link(cg0, tok);
    if (j & 1) { stsm4t(stg_lane + (j - 1) * 1024, plo, phi_, lo, hi); if (j < 10) tok = token(zaddr); }
    if ((j + 1) % CH_F == 0 && j < 11) { chain(cg0, lo, zero); chain(cu0, lo, zero); chain(cg1, hi, zero); chain(cu1, hi, zero); }
    plo = lo; phi_ = hi;
  }
}

__device__ __forceinline__ void consumer(const Params& p, uint32_t sb, int b, int wg, int tid) {
  int G, rb;
  role1(b, G, rb);
  const int lane = tid & 31, wq = tid >> 5;
  const int mi = lane >> 3, r8 = lane & 7;
  uint32_t stg_lane = sb + SOFF + (8 * (mi >> 1) + r8) * 128 + (((2 * wq + (mi & 1)) ^ r8) << 4);
  asm volatile("mov.u32 %0, %0;" : "+r"(stg_lane));
  const uint32_t zero = p.zero;
  if (wg == 1) ln_stats(sb, tid, G, rb, p.sy);
  {
    float a0[48], a1[48], st[48];
#pragma unroll 1
    for (int s = wg; s < 7; s += 2) {
      float kv[32];
#pragma unroll
      for (int i = 0; i < 48; i++) { a0[i] = 0.f; a1[i] = 0.f; }
#pragma unroll
      for (int i = 0; i < 32; i++) kv[i] = 0.f;
      keep(a0); keep(a1); keep(kv);
      const uint32_t rot = s >= 4;
      const uint32_t alA = dlo(WOFF) + rot * (3 * 1024), alB = dlo(WOFF) - rot * (2 * 1024);
      const uint32_t fbA = sb + B_FULL + rot * 24, fbB = sb + B_FULL - rot * 16;
      uint32_t eb = sb + B_DUMMY;
      if (s > 0) bar_sync(1 + wg, 256);
      if (tid == 0) STAMP(3 * s);
#pragma unroll 1
      for (uint32_t h = 0; h < 2; h++) {
        const uint32_t blo = dlo(XOFF) + h * (5 * XCH >> 4);
#pragma unroll
        for (int j = 0; j < 5; j++) {
          const uint32_t alo = (j < 2 ? alA : alB) + j * 1024, fb = (j < 2 ? fbA : fbB) + 8 * j;
          if (s == 0) mbar_wait(sb + B_XFULL + 40 * h + 8 * j, 0);
          mbar_wait(fb, j < 2 ? h : h ^ rot);
          wg_fence();
#pragma unroll
          for (int kk = 0; kk < 4; kk++) {
            wgmma_n96(a0, alo + kk * 128, blo + j * (XCH >> 4) + kk * 2, 1);
            wgmma_n96(a1, alo + 512 + kk * 128, blo + j * (XCH >> 4) + kk * 2, 1);
          }
          wg_commit();
          wg_wait<1>();
          arrive_elect(eb);
          eb = fb + (B_EMPTY - B_FULL);
        }
      }
      if (s == 3) {
#pragma unroll
        for (int j = 0; j < 3; j++) {
          mbar_wait(sb + B_FULL + 8 * j, 0);
          wg_fence();
#pragma unroll
          for (int kk = 0; kk < 4; kk++) wgmma_n64_kk(kv, dlo(WOFF) + j * 1024 + kk * 2, dlo(WOFF) + j * 1024 + 512 + kk * 2, 1);
          wg_commit();
        }
        bar_arrive(1, 256);
        wg_wait<3>(); arrive_elect(eb);
        wg_wait<2>(); arrive_elect(sb + B_EMPTY);
        wg_wait<1>(); arrive_elect(sb + B_EMPTY + 8);
        eb = sb + B_EMPTY + 16;
      } else if (s < 6) bar_arrive(2 - wg, 256);
      wg_wait<0>();
      keep(a0); keep(a1);
      arrive_elect(eb);
      if (tid == 0) STAMP(3 * s + 1);
      if (s == 3 && b < NKVC) {
        keep(kv);
        const int hg = b / 11, part = b - 11 * hg;
#pragma unroll
        for (int hf = 0; hf < 2; hf++) {
          const int r = 16 * wq + (lane >> 2) + 8 * hf, hl = r / 20, head = 3 * hg + hl;
          if (hl < 3 && head < 32) {
            float* dst = p.kvp + (head * 11 + part) * 400 + (r - 20 * hl) * 20 - 20 * hl + 2 * (lane & 3);
#pragma unroll
            for (int j = 0; j < 8; j++)
              if ((unsigned)(8 * j + 2 * (lane & 3) - 20 * hl) < 20u) *reinterpret_cast<float2*>(dst + 8 * j) = make_float2(kv[4 * j + 2 * hf], kv[4 * j + 2 * hf + 1]);
            if ((lane & 3) == 2) p.zp[part * D_ + 60 * hg + r] = kv[28 + 2 * hf];
          }
        }
        mbar_arrive(sb + B_KVF);
      }
      if (s < 2) load_stats(st, sb, lane);
      int ix;
      const int ty = step_info(G, s, ix);
      if (s > 0) mbar_wait(sb + B_STG + 8 * (1 - wg), ((s - 1) >> 1) & 1);
      if (ty == T_KV) {
        const uint32_t row = 16 * wq + 8 * (mi & 1) + r8;
        const uint32_t dA = sb + SOFF + row * 128 + (((mi >> 1) ^ r8) << 4), dB = sb + SOFF + 8192 + row * 64 + (((mi >> 1) ^ (r8 >> 1)) << 4);
        epi_attn<false, false>(a1, st, lane, zero, sb + W_ZERO, dA + XCH, dB + XCH);
        epi_attn<true, false>(a0, st, lane, zero, sb + W_ZERO, dA, dB);
      } else if (ty == T_QQ) {
        epi_attn<true, true>(a0, st, lane, zero, sb + W_ZERO, stg_lane, 0);
        epi_attn<true, true>(a1, st, lane, zero, sb + W_ZERO, stg_lane + XCH, 0);
      } else epi_ffn(a0, a1, st, lane, zero, sb + W_ZERO, stg_lane);
      fence_async_smem();
      mbar_arrive(sb + B_STGF + 8 * wg);
      if (tid == 0) STAMP(3 * s + 2);
    }
  }
  if (b >= 130) return;
  const int tb = b / 5, cg = b - tb * 5;
  float o[40], sa[40], gt[40];
  uint32_t slot = 0, par = 0, eb = sb + B_DUMMY;
  const bool do_m = wg == 1 && b < NMC;
  if (tid == 0) STAMP(24 + 4 * wg);
  int i = 0;
#pragma unroll 1
  for (int iend = 4; iend <= 27; iend += 23) {
#pragma unroll 1
    for (; i < iend; i++) {
      const uint32_t blo = dlo(16384) + (p2_stage(slot) >> 4), alo = blo - 1024 + wg * 512;
      mbar_wait(sb + B_FULL2 + 8 * slot, par);
      if (i == 0 && tid == 0) STAMP(25 + 4 * wg);
      wg_fence();
#pragma unroll
      for (int kk = 0; kk < 4; kk++) wgmma_n80(o, alo + kk * 128, blo + kk * 2, kk ? 1 : i);
      wg_commit();
      wg_wait<1>();
      arrive_elect(eb);
      eb = sb + B_EMPTY2 + 8 * slot;
      if (++slot == NS2) { slot = 0; par ^= 1; }
    }
    if (do_m && iend == 4) {
      float m[32];
      mbar_wait(sb + B_WO, 0);
      wg_fence();
#pragma unroll
      for (int kk = 0; kk < 4; kk++) wgmma_n64(m, dlo(WOOFF) + kk * 128, dlo(WOOFF + 8192) + kk * 2, kk);
      wg_commit();
      wg_wait<0>();
      keep(m);
      bar_sync(4, 128);
#pragma unroll
      for (int j = 0; j < 4; j++)
        stsm4t(stg_lane + (WOOFF + 8192 - SOFF) + j * 2048, pack2(m[8 * j], m[8 * j + 1]), pack2(m[8 * j + 2], m[8 * j + 3]),
               pack2(m[8 * j + 4], m[8 * j + 5]), pack2(m[8 * j + 6], m[8 * j + 7]));
      fence_async_smem();
      mbar_arrive(sb + B_MF);
    }
  }
#pragma unroll 1
  for (int i = 0; i < 10; i++) {
    const uint32_t blo = dlo(16384) + (p2_stage(slot) >> 4), alo = blo - 1024 + wg * 512;
    mbar_wait(sb + B_FULL2 + 8 * slot, par);
    wg_fence();
#pragma unroll
    for (int kk = 0; kk < 4; kk++) wgmma_n80(sa, alo + kk * 128, blo + kk * 2, kk ? 1 : i);
    wg_commit();
    wg_wait<1>();
    arrive_elect(eb);
    if (i == 4 * wg) {
      keep(o);
#pragma unroll
      for (int q = 0; q < 40; q++) gt[q] = silu(o[q]);
    }
    eb = sb + B_EMPTY2 + 8 * slot;
    if (++slot == NS2) { slot = 0; par ^= 1; }
  }
  uint32_t xr[20];
  mbar_wait(sb + B_XRES, 0);
  const uint32_t ob = stg_lane + wg * XCH;
#pragma unroll
  for (int j = 0; j < 5; j++) ldsm4t(ob + j * 2048, xr[4 * j], xr[4 * j + 1], xr[4 * j + 2], xr[4 * j + 3]);
  wg_wait<0>();
  keep(sa);
  if (tid == 0) STAMP(26 + 4 * wg);
#pragma unroll
  for (int j = 0; j < 5; j++) {
    uint32_t r[4];
#pragma unroll
    for (int q = 0; q < 4; q++) {
      const int e = 8 * j + 2 * q;
      r[q] = pack2(fmaf(sa[e], gt[e], bf_lo(xr[4 * j + q])), fmaf(sa[e + 1], gt[e + 1], bf_hi(xr[4 * j + q])));
    }
    stsm4t(ob + j * 2048, r[0], r[1], r[2], r[3]);
  }
  fence_async_smem();
  bar_sync(3 + wg, 128);
  if (tid == 0) {
    tma_st(&p.out, cg * 128 + wg * 64, tb * 80, sb + SOFF + wg * XCH);
    bulk_commit();
    bulk_wait_read();
    STAMP(27 + 4 * wg);
  }
}

__global__ void __launch_bounds__(384, 1) fused_kernel(const __grid_constant__ Params p) {
  extern __shared__ __align__(1024) unsigned char smem[];
  uint32_t sb = (uint32_t)__cvta_generic_to_shared(smem);
  asm volatile("mov.u32 %0, %0;" : "+r"(sb));
  const int b = blockIdx.x;
  const int warp = __shfl_sync(0xffffffffu, threadIdx.x >> 5, 0), lane = threadIdx.x & 31;
  if (warp == 8) {
    int G, rb;
    role1(b, G, rb);
    const int c0 = (G == 5) ? 256 : 640 + 128 * G, c1 = c0 + (G == 5 ? 64 : 640);
    if (elect_one()) {
      STAMP(48);
#pragma unroll
      for (int i = 0; i < NS1; i++) mbar_init(sb + B_FULL + 8 * i, 1);
#pragma unroll
      for (int i = 0; i < 10; i++) mbar_init(sb + B_XFULL + 8 * i, 1);
      fence_async_smem();
    }
    __syncwarp();
    expect_e(sb + B_FULL, 16384);
    tma_ld_e(sb + WOFF, &p.wqkv, c0, 0, sb + B_FULL);
    tma_ld_e(sb + WOFF + 8192, &p.wqkv, c1, 0, sb + B_FULL);
    expect_e(sb + B_XFULL, TB * 128);
    tma_ld_e(sb + XOFF, &p.x1, 0, rb * TB, sb + B_XFULL);
  } else if (warp == 9) {
    if (elect_one()) {
#pragma unroll
      for (int i = 0; i < NS1; i++) mbar_init(sb + B_EMPTY + 8 * i, 4);
#pragma unroll
      for (int i = 20; i < 47; i++) mbar_init(sb + MOFF + 8 * i, (i >= 27 && i < 34) ? 8 : ((i == 34) ? 32 : ((i >= 38 && i < 43) ? 128 : 1)));
      sts64v(sb + W_READY, 0); sts64v(sb + W_B, 0);
      if ((sb & 0x3FFFF) != 1024) TRAP(0);
      fence_async_smem();
    }
  } else if (threadIdx.x < 160) {
    const int i = threadIdx.x;
    sts128(sb + XOFF + (i >> 4) * XCH + TB * 128 + (i & 15) * 16, make_uint4(0x3F803F80u, 0x3F803F80u, 0x3F803F80u, 0x3F803F80u));
    fence_async_smem();
  }
  __syncthreads();
  if (threadIdx.x == 0) STAMP(57);
  if (warp >= 8) {
    asm volatile("setmaxnreg.dec.sync.aligned.u32 88;");
    if (warp == 8) producer(p, sb, b, lane);
    else if (warp == 9) agent(p, sb, b, lane);
    else aux(p, sb, b, warp - 10, lane);
  } else {
    asm volatile("setmaxnreg.inc.sync.aligned.u32 208;");
    consumer(p, sb, b, warp >> 2, threadIdx.x & 127);
  }
}

typedef CUresult (*EncodeFn)(CUtensorMap*, CUtensorMapDataType, cuuint32_t, void*, const cuuint64_t*, const cuuint64_t*,
                             const cuuint32_t*, const cuuint32_t*, CUtensorMapInterleave, CUtensorMapSwizzle,
                             CUtensorMapL2promotion, CUtensorMapFloatOOBfill);

void make_map(EncodeFn enc, CUtensorMap* m, const void* ptr, uint64_t rows, uint64_t cols, uint32_t box_rows, uint32_t box_cols = 64) {
  cuuint64_t gd[2] = {cols, rows}, gs[1] = {cols * 2};
  cuuint32_t bd[2] = {box_cols, box_rows}, es[2] = {1, 1};
  CUresult r = enc(m, CU_TENSOR_MAP_DATA_TYPE_BFLOAT16, 2, const_cast<void*>(ptr), gd, gs, bd, es, CU_TENSOR_MAP_INTERLEAVE_NONE,
                   box_cols == 64 ? CU_TENSOR_MAP_SWIZZLE_128B : CU_TENSOR_MAP_SWIZZLE_64B, CU_TENSOR_MAP_L2_PROMOTION_L2_128B, CU_TENSOR_MAP_FLOAT_OOB_FILL_NONE);
  if (r != CUDA_SUCCESS) fprintf(stderr, "cuTensorMapEncodeTiled failed: %d\n", (int)r);
}

}

extern "C" void kernel_launch(void* const* d_in, const int* in_sizes, int n_in, void* d_out, int out_size) {
  (void)in_sizes; (void)n_in; (void)out_size;
  static EncodeFn enc = nullptr;
  static void *pH = nullptr, *pPQ = nullptr, *pM = nullptr, *pKV = nullptr, *pKvp = nullptr, *pZp = nullptr, *pSy = nullptr,
              *pMask = nullptr, *pB = nullptr, *pZ = nullptr;
  if (!enc) {
    void* fn = nullptr;
    cudaDriverEntryPointQueryResult st;
    cudaGetDriverEntryPoint("cuTensorMapEncodeTiled", &fn, cudaEnableDefault, &st);
    enc = (EncodeFn)fn;
    cudaGetSymbolAddress(&pH, g_H); cudaGetSymbolAddress(&pPQ, g_PQ); cudaGetSymbolAddress(&pM, g_M); cudaGetSymbolAddress(&pKV, g_KVT);
    cudaGetSymbolAddress(&pKvp, g_kvp); cudaGetSymbolAddress(&pZp, g_zp); cudaGetSymbolAddress(&pSy, g_sync);
    cudaGetSymbolAddress(&pMask, g_mask); cudaGetSymbolAddress(&pB, g_B); cudaGetSymbolAddress(&pZ, g_z);
    cudaFuncSetAttribute(fused_kernel, cudaFuncAttributeMaxDynamicSharedMemorySize, SMEM_BYTES);
  }
  Params p;
  const void *x = d_in[0], *wqkv = d_in[1], *wo = d_in[2], *w1 = d_in[4], *w3 = d_in[5], *w2 = d_in[6];
  make_map(enc, &p.x1, x, S_, D_, TB);
  make_map(enc, &p.wqkv, wqkv, D_, 3 * D_, 64);
  make_map(enc, &p.w1, w1, D_, F_, 64);
  make_map(enc, &p.w3, w3, D_, F_, 64);
  make_map(enc, &p.hst, pH, S_, F_, TB);
  make_map(enc, &p.pqst, pPQ, S_, D_, TB);
  make_map(enc, &p.w2, w2, F_, D_, 64);
  make_map(enc, &p.mm, pM, D_, D_, 64);
  make_map(enc, &p.hld, pH, S_, F_, 80);
  make_map(enc, &p.ald, pPQ, S_, D_, 80);
  make_map(enc, &p.xres, x, S_, D_, 80);
  make_map(enc, &p.out, d_out, S_, D_, 80);
  make_map(enc, &p.kva, pKV, 2 * D_, KTP, 64);
  make_map(enc, &p.kvb, pKV, 2 * D_, KTP, 64, 32);
  make_map(enc, &p.vld, pKV, 2 * D_, KTP, 60);
  make_map(enc, &p.msk, pMask, 4, KTP, 4);
  make_map(enc, &p.bld, pB, 11 * 64, 64, 64);
  make_map(enc, &p.wom, wo, D_, D_, 64);
  make_map(enc, &p.mst, pM, D_, D_, 60);
  p.wo = (const __nv_bfloat16*)wo;
  p.w2p = (const __nv_bfloat16*)w2;
  p.mask_p = (__nv_bfloat16*)pMask; p.b_p = (__nv_bfloat16*)pB; p.z = (float*)pZ; p.pq_p = (__nv_bfloat16*)pPQ;
  p.zero = 0;
  p.kvp = (float*)pKvp; p.zp = (float*)pZp; p.sy = (Sync*)pSy;
  fused_kernel<<<NCTA, 384, SMEM_BYTES>>>(p);
}
```

```cpp
#include <cuda_runtime.h>
#include <cuda_bf16.h>
#include <cuda.h>
#include <stdint.h>
#include <stdio.h>
#include <math.h>

namespace {

constexpr int S_ = 2048, D_ = 640, F_ = 1728;
constexpr int TB = 94;
constexpr int NRB = 22;
constexpr int NCTA = 132;
constexpr int KTP = NRB * 96;
constexpr int NKVC = 121;
constexpr int NMC = 110;
constexpr int NS1 = 5;
constexpr int NS2 = 8;
constexpr uint32_t ST2 = 26624;
constexpr int NK2 = 37;

constexpr uint32_t XOFF = 0;
constexpr uint32_t XCH = 12288;
constexpr uint32_t WOFF = 122880;
constexpr uint32_t SOFF = 204800;
constexpr uint32_t MOFF = 229376;
enum {
  I_FULL = 0, I_XFULL = 5, I_EMPTY = 15, I_FULL2 = 20, I_EMPTY2 = 28, I_STATS = 36, I_XRES, I_STG, I_STGF = I_STG + 2, I_KVF = I_STGF + 2,
  I_MF, I_DUMMY, I_WO, I_AL, I_Z, I_PD, I_T1, I_T6, I_S1F, I_S1E, I_S7, I_END
};
constexpr uint32_t B_FULL = MOFF + 8 * I_FULL;
constexpr uint32_t B_XFULL = MOFF + 8 * I_XFULL;
constexpr uint32_t B_EMPTY = MOFF + 8 * I_EMPTY;
constexpr uint32_t B_FULL2 = MOFF + 8 * I_FULL2;
constexpr uint32_t B_EMPTY2 = MOFF + 8 * I_EMPTY2;
constexpr uint32_t B_STATS = MOFF + 8 * I_STATS;
constexpr uint32_t B_XRES = MOFF + 8 * I_XRES;
constexpr uint32_t B_STG = MOFF + 8 * I_STG;
constexpr uint32_t B_STGF = MOFF + 8 * I_STGF;
constexpr uint32_t B_KVF = MOFF + 8 * I_KVF;
constexpr uint32_t B_MF = MOFF + 8 * I_MF;
constexpr uint32_t B_DUMMY = MOFF + 8 * I_DUMMY;
constexpr uint32_t B_WO = MOFF + 8 * I_WO;
constexpr uint32_t B_AL = MOFF + 8 * I_AL;
constexpr uint32_t B_Z = MOFF + 8 * I_Z;
constexpr uint32_t B_PD = MOFF + 8 * I_PD;
constexpr uint32_t B_T1 = MOFF + 8 * I_T1;
constexpr uint32_t B_T6 = MOFF + 8 * I_T6;
constexpr uint32_t B_S1F = MOFF + 8 * I_S1F;
constexpr uint32_t B_S1E = MOFF + 8 * I_S1E;
constexpr uint32_t B_S7 = MOFF + 8 * I_S7;
constexpr uint32_t W_READY = MOFF + 448;
constexpr uint32_t W_KV = MOFF + 452;
constexpr uint32_t W_B = MOFF + 456;
constexpr uint32_t W_ZERO = MOFF + 460;
constexpr uint32_t STATS = MOFF + 464;
static_assert(8 * I_END <= 448 && I_S7 - I_EMPTY <= 39, "barriers");
constexpr uint32_t ZS = STATS;
constexpr uint32_t SMEM_BYTES = ZS + 2560;
constexpr uint32_t WOOFF = 7 * ST2;
constexpr uint32_t XROFF = 6 * ST2;
static_assert(SMEM_BYTES <= 232448, "smem");

#define KVS_ 3
#define PACE0 400
#define PACE 330
#define PACE2 320
#define T0_DELAY 5200
#define T0_LEAD 400

struct Sync {
  unsigned long long stats[NRB * 96];
  unsigned hflag[NRB * 32];
  unsigned tslot[160];
  unsigned c_kv[32], c_q[32], c_p[32], c_b[32], c_m[32], c_done[32];
  unsigned c_a[32];
};

__device__ __align__(1024) __nv_bfloat16 g_H[S_ * F_];
__device__ __align__(1024) __nv_bfloat16 g_PQ[S_ * D_];
__device__ __align__(1024) __nv_bfloat16 g_M[D_ * D_];
__device__ __align__(1024) __nv_bfloat16 g_KVT[2 * D_ * KTP];
__device__ __align__(1024) __nv_bfloat16 g_mask[4 * KTP];
__device__ __align__(1024) __nv_bfloat16 g_B[11 * 64 * 64];
__device__ __align__(1024) float g_z[D_];
__device__ __align__(1024) float g_kvp[32 * 11 * 400];
__device__ __align__(1024) float g_zp[11 * D_];
__device__ __align__(1024) Sync g_sync;
#define STAMP(i) do {} while (0)

#define TRAP(id) __trap()

struct Params {
  CUtensorMap x1, wqkv, w1, w3, hst, pqst, w2, mm, hld, ald, xres, out, kva, kvb, vld, msk, wom, bld, mst;
  const __nv_bfloat16* wo;
  const __nv_bfloat16* w2p;
  __nv_bfloat16 *mask_p, *pq_p, *b_p;
  float *kvp, *zp, *z;
  Sync* sy;
  uint32_t zero;
};

__device__ __forceinline__ unsigned long long gtime() { unsigned long long g; asm volatile("mov.u64 %0, %%globaltimer;" : "=l"(g)::"memory"); return g; }
__device__ __forceinline__ uint32_t gtime32() { uint32_t g; asm volatile("mov.u32 %0, %%globaltimer_lo;" : "=r"(g)::"memory"); return g; }
__device__ __forceinline__ uint32_t clk32() { uint32_t c; asm volatile("mov.u32 %0, %%clock;" : "=r"(c)::"memory"); return c; }
__device__ __forceinline__ bool elect_one() { uint32_t p; asm volatile("{.reg .pred P; elect.sync _|P, 0xffffffff; selp.u32 %0,1,0,P;}" : "=r"(p)); return p; }
__device__ __forceinline__ void mbar_init(uint32_t bar, uint32_t cnt) { asm volatile("mbarrier.init.shared::cta.b64 [%0], %1;" ::"r"(bar), "r"(cnt) : "memory"); }
__device__ __forceinline__ void mbar_expect_tx(uint32_t bar, uint32_t bytes) { asm volatile("mbarrier.arrive.expect_tx.shared::cta.b64 _, [%0], %1;" ::"r"(bar), "r"(bytes) : "memory"); }
__device__ __forceinline__ void mbar_arrive(uint32_t bar) { asm volatile("mbarrier.arrive.shared::cta.b64 _, [%0];" ::"r"(bar) : "memory"); }
__device__ __forceinline__ bool mbar_test(uint32_t bar, uint32_t parity) {
  uint32_t ok;
  asm volatile("{.reg .pred p; mbarrier.test_wait.parity.shared::cta.b64 p, [%1], %2; selp.u32 %0,1,0,p;}" : "=r"(ok) : "r"(bar), "r"(parity) : "memory");
  return ok;
}
__device__ __forceinline__ bool mbar_try(uint32_t bar, uint32_t parity) {
  uint32_t ok;
  asm volatile("{.reg .pred p; mbarrier.try_wait.parity.shared::cta.b64 p, [%1], %2; selp.u32 %0,1,0,p;}" : "=r"(ok) : "r"(bar), "r"(parity) : "memory");
  return ok;
}
constexpr uint32_t SPIN_LIMIT = 1u << 22;
__device__ __forceinline__ void mbar_wait(uint32_t bar, uint32_t parity) {
  asm volatile("{\n.reg .pred p;\n.reg .u32 c;\nmov.u32 c, 0;\n"
               "LW:\nmbarrier.try_wait.parity.shared::cta.b64 p, [%0], %1;\n@p bra LD;\n"
               "add.u32 c, c, 1;\nsetp.lt.u32 p, c, %2;\n@p bra LW;\ntrap;\nLD:\n}" ::"r"(bar), "r"(parity), "n"(SPIN_LIMIT) : "memory");
}
__device__ __forceinline__ void tma_ld(uint32_t dst, const CUtensorMap* m, int c0, int c1, uint32_t bar) {
  asm volatile("cp.async.bulk.tensor.2d.shared::cluster.global.mbarrier::complete_tx::bytes [%0], [%1, {%3,%4}], [%2];"
               ::"r"(dst), "l"(m), "r"(bar), "r"(c0), "r"(c1) : "memory");
}
__device__ __forceinline__ void expect_e(uint32_t bar, uint32_t bytes) {
  asm volatile("{.reg .pred P; elect.sync _|P, 0xffffffff; @P mbarrier.arrive.expect_tx.shared::cta.b64 _, [%0], %1;}" ::"r"(bar), "r"(bytes) : "memory");
}
__device__ __forceinline__ void tma_ld_e(uint32_t dst, const CUtensorMap* m, int c0, int c1, uint32_t bar) {
  asm volatile("{.reg .pred P; elect.sync _|P, 0xffffffff;\n"
               "@P cp.async.bulk.tensor.2d.shared::cluster.global.mbarrier::complete_tx::bytes [%0], [%1, {%3,%4}], [%2];}"
               ::"r"(dst), "l"(m), "r"(bar), "r"(c0), "r"(c1) : "memory");
}
__device__ __forceinline__ void tma_ld3_e(uint32_t dst, const CUtensorMap* m, int c1, int c2, uint32_t bar) {
  asm volatile("{.reg .pred P; elect.sync _|P, 0xffffffff;\n"
               "@P cp.async.bulk.tensor.3d.shared::cluster.global.mbarrier::complete_tx::bytes [%0], [%1, {0,%3,%4}], [%2];}"
               ::"r"(dst), "l"(m), "r"(bar), "r"(c1), "r"(c2) : "memory");
}
__device__ __forceinline__ void tma_st(const CUtensorMap* m, int c0, int c1, uint32_t src) {
  asm volatile("cp.async.bulk.tensor.2d.global.shared::cta.bulk_group [%0, {%2,%3}], [%1];" ::"l"(m), "r"(src), "r"(c0), "r"(c1) : "memory");
}
__device__ __forceinline__ void bulk_ld(uint32_t dst, const void* src, uint32_t bytes, uint32_t bar) {
  asm volatile("cp.async.bulk.shared::cluster.global.mbarrier::complete_tx::bytes [%0], [%1], %2, [%3];" ::"r"(dst), "l"(src), "r"(bytes), "r"(bar) : "memory");
}
__device__ __forceinline__ void bulk_st(void* dst, uint32_t src, uint32_t bytes) {
  asm volatile("cp.async.bulk.global.shared::cta.bulk_group [%0], [%1], %2;" ::"l"(dst), "r"(src), "r"(bytes) : "memory");
}
__device__ __forceinline__ void tma_pf(const CUtensorMap* m, int c0, int c1) {
  asm volatile("cp.async.bulk.prefetch.tensor.2d.L2.global.tile [%0, {%1,%2}];" ::"l"(m), "r"(c0), "r"(c1) : "memory");
}
__device__ __forceinline__ void bulk_pf(const void* p, uint32_t bytes) { asm volatile("cp.async.bulk.prefetch.L2.global [%0], %1;" ::"l"(p), "r"(bytes) : "memory"); }
__device__ __forceinline__ void desc_pf(const CUtensorMap* m) { asm volatile("prefetch.tensormap [%0];" ::"l"(m) : "memory"); }
__device__ __forceinline__ void bulk_commit() { asm volatile("cp.async.bulk.commit_group;" ::: "memory"); }
__device__ __forceinline__ void bulk_wait_read() { asm volatile("cp.async.bulk.wait_group.read 0;" ::: "memory"); }
__device__ __forceinline__ void bulk_wait_all() { asm volatile("cp.async.bulk.wait_group 0;" ::: "memory"); }
__device__ __forceinline__ void fence_async_smem() { asm volatile("fence.proxy.async.shared::cta;" ::: "memory"); }
__device__ __forceinline__ void fence_async_global() { asm volatile("fence.proxy.async.global;" ::: "memory"); }
__device__ __forceinline__ void bar_sync(int id, int n) { asm volatile("bar.sync %0, %1;" ::"r"(id), "r"(n) : "memory"); }
__device__ __forceinline__ void bar_arrive(int id, int n) { asm volatile("bar.arrive %0, %1;" ::"r"(id), "r"(n) : "memory"); }
__device__ __forceinline__ void wg_fence() { asm volatile("wgmma.fence.sync.aligned;" ::: "memory"); }
__device__ __forceinline__ void wg_commit() { asm volatile("wgmma.commit_group.sync.aligned;" ::: "memory"); }
template <int N> __device__ __forceinline__ void wg_wait() { asm volatile("wgmma.wait_group.sync.aligned %0;" ::"n"(N) : "memory"); }
template <int N> __device__ __forceinline__ void keep(float (&d)[N]) {
#pragma unroll
  for (int i = 0; i < N; i++) asm volatile("" : "+f"(d[i])::"memory");
}
__device__ __forceinline__ unsigned ld_rlx(const unsigned* p) { unsigned v; asm volatile("ld.relaxed.gpu.global.u32 %0, [%1];" : "=r"(v) : "l"(p) : "memory"); return v; }
__device__ __forceinline__ unsigned long long ld_rlx64(const unsigned long long* p) { unsigned long long v; asm volatile("ld.relaxed.gpu.global.u64 %0, [%1];" : "=l"(v) : "l"(p) : "memory"); return v; }
__device__ __forceinline__ void st_rlx(unsigned* p, unsigned v) { asm volatile("st.relaxed.gpu.global.u32 [%0], %1;" ::"l"(p), "r"(v) : "memory"); }
__device__ __forceinline__ void st_rlx64(unsigned long long* p, unsigned long long v) { asm volatile("st.relaxed.gpu.global.u64 [%0], %1;" ::"l"(p), "l"(v) : "memory"); }
__device__ __forceinline__ void fence_acq() { asm volatile("fence.acquire.gpu;" ::: "memory"); }
__device__ __forceinline__ void red_rlx(unsigned* p, unsigned v) { asm volatile("red.relaxed.gpu.global.add.u32 [%0], %1;" ::"l"(p), "r"(v) : "memory"); }
__device__ __forceinline__ void red_rel(unsigned* p, unsigned v) { asm volatile("red.release.gpu.global.add.u32 [%0], %1;" ::"l"(p), "r"(v) : "memory"); }
__device__ __forceinline__ unsigned lds_acq(uint32_t a) { unsigned v; asm volatile("ld.acquire.cta.shared::cta.u32 %0, [%1];" : "=r"(v) : "r"(a) : "memory"); return v; }
__device__ __forceinline__ void sts_rel(uint32_t a, unsigned v) { asm volatile("st.release.cta.shared::cta.u32 [%0], %1;" ::"r"(a), "r"(v) : "memory"); }
__device__ __forceinline__ unsigned long long lds64v(uint32_t a) { unsigned long long v; asm volatile("ld.volatile.shared::cta.u64 %0, [%1];" : "=l"(v) : "r"(a) : "memory"); return v; }
__device__ __forceinline__ void sts64v(uint32_t a, unsigned long long v) { asm volatile("st.volatile.shared::cta.u64 [%0], %1;" ::"r"(a), "l"(v) : "memory"); }
__device__ __forceinline__ uint4 lds128(uint32_t a) { uint4 v; asm volatile("ld.shared.v4.u32 {%0,%1,%2,%3}, [%4];" : "=r"(v.x), "=r"(v.y), "=r"(v.z), "=r"(v.w) : "r"(a) : "memory"); return v; }
__device__ __forceinline__ float4 lds128f(uint32_t a) { float4 v; asm volatile("ld.shared.v4.f32 {%0,%1,%2,%3}, [%4];" : "=f"(v.x), "=f"(v.y), "=f"(v.z), "=f"(v.w) : "r"(a) : "memory"); return v; }
__device__ __forceinline__ void sts128(uint32_t a, uint4 v) { asm volatile("st.shared.v4.u32 [%0], {%1,%2,%3,%4};" ::"r"(a), "r"(v.x), "r"(v.y), "r"(v.z), "r"(v.w) : "memory"); }
__device__ __forceinline__ void stsm4t(uint32_t a, uint32_t r0, uint32_t r1, uint32_t r2, uint32_t r3) {
  asm volatile("stmatrix.sync.aligned.m8n8.x4.trans.shared.b16 [%0], {%1,%2,%3,%4};" ::"r"(a), "r"(r0), "r"(r1), "r"(r2), "r"(r3) : "memory");
}
__device__ __forceinline__ void stsm4(uint32_t a, uint32_t r0, uint32_t r1, uint32_t r2, uint32_t r3) {
  asm volatile("stmatrix.sync.aligned.m8n8.x4.shared.b16 [%0], {%1,%2,%3,%4};" ::"r"(a), "r"(r0), "r"(r1), "r"(r2), "r"(r3) : "memory");
}
__device__ __forceinline__ void ldsm4t(uint32_t a, uint32_t& r0, uint32_t& r1, uint32_t& r2, uint32_t& r3) {
  asm volatile("ldmatrix.sync.aligned.m8n8.x4.trans.shared.b16 {%0,%1,%2,%3}, [%4];" : "=r"(r0), "=r"(r1), "=r"(r2), "=r"(r3) : "r"(a) : "memory");
}
__device__ __forceinline__ uint32_t pack2(float lo, float hi) { uint32_t r; asm("cvt.rn.bf16x2.f32 %0, %1, %2;" : "=r"(r) : "f"(hi), "f"(lo)); return r; }
__device__ __forceinline__ float bf_lo(uint32_t v) { return __uint_as_float(v << 16); }
__device__ __forceinline__ float bf_hi(uint32_t v) { return __uint_as_float(v & 0xffff0000u); }
__device__ __forceinline__ float ex2(float x) { float y; asm("ex2.approx.ftz.f32 %0, %1;" : "=f"(y) : "f"(x)); return y; }
__device__ __forceinline__ float rcp(float x) { float y; asm("rcp.approx.ftz.f32 %0, %1;" : "=f"(y) : "f"(x)); return y; }
constexpr float LOG2E = 1.4426950408889634f, LN2 = 0.6931471805599453f;
__device__ __forceinline__ float silu(float g) { return g * rcp(1.f + ex2(g * -1.4426950408889634f)); }
__device__ __forceinline__ float phi_l(float yl) { return fmaxf(fmaf(yl, LN2, 1.000001f), __saturatef(ex2(yl) + 1e-6f)); }
__host__ __device__ constexpr uint32_t dlo(uint32_t off) { return ((1024u + off) >> 4) | (1u << 16); }
__device__ __forceinline__ void arrive_elect(uint32_t bar) {
  asm volatile("{.reg .pred P; elect.sync _|P, 0xffffffff; @P mbarrier.arrive.shared::cta.b64 _, [%0];}" ::"r"(bar) : "memory");
}
__device__ __forceinline__ void wait_count(const unsigned* p, unsigned target) {
  if ((threadIdx.x & 31) == 0) {
    uint32_t c = 0;
    while (ld_rlx(p) < target) { if (++c > SPIN_LIMIT) TRAP(target); }
    fence_acq();
  }
  __syncwarp();
}

__device__ __forceinline__ void wgmma_n96_first(float (&d)[48], uint32_t da, uint32_t db) {
  asm volatile("{.reg .pred p; .reg .b64 da, db; setp.ne.b32 p, 0, 0;\n"
    "mov.b64 da, {%48, 0x40000040}; mov.b64 db, {%49, 0x40000040};\n"
    "wgmma.mma_async.sync.aligned.m64n96k16.f32.bf16.bf16 "
    "{%0, %1, %2, %3, %4, %5, %6, %7, %8, %9, %10, %11, %12, %13, %14, %15, "
    "%16, %17, %18, %19, %20, %21, %22, %23, %24, %25, %26, %27, %28, %29, %30, %31, "
    "%32, %33, %34, %35, %36, %37, %38, %39, %40, %41, %42, %43, %44, %45, %46, %47}, "
    "da, db, p, 1, 1, 1, 0;}"
    : "=f"(d[0]), "=f"(d[1]), "=f"(d[2]), "=f"(d[3]), "=f"(d[4]), "=f"(d[5]), "=f"(d[6]), "=f"(d[7]),
      "=f"(d[8]), "=f"(d[9]), "=f"(d[10]), "=f"(d[11]), "=f"(d[12]), "=f"(d[13]), "=f"(d[14]), "=f"(d[15]),
      "=f"(d[16]), "=f"(d[17]), "=f"(d[18]), "=f"(d[19]), "=f"(d[20]), "=f"(d[21]), "=f"(d[22]), "=f"(d[23]),
      "=f"(d[24]), "=f"(d[25]), "=f"(d[26]), "=f"(d[27]), "=f"(d[28]), "=f"(d[29]), "=f"(d[30]), "=f"(d[31]),
      "=f"(d[32]), "=f"(d[33]), "=f"(d[34]), "=f"(d[35]), "=f"(d[36]), "=f"(d[37]), "=f"(d[38]), "=f"(d[39]),
      "=f"(d[40]), "=f"(d[41]), "=f"(d[42]), "=f"(d[43]), "=f"(d[44]), "=f"(d[45]), "=f"(d[46]), "=f"(d[47])
    : "r"(da), "r"(db));
}
__device__ __forceinline__ void wgmma_n64_kk_first(float (&d)[32], uint32_t da, uint32_t db) {
  asm volatile("{.reg .pred p; .reg .b64 da, db; setp.ne.b32 p, 0, 0;\n"
    "mov.b64 da, {%32, 0x40000040}; mov.b64 db, {%33, 0x40000040};\n"
    "wgmma.mma_async.sync.aligned.m64n64k16.f32.bf16.bf16 "
    "{%0, %1, %2, %3, %4, %5, %6, %7, %8, %9, %10, %11, %12, %13, %14, %15, "
    "%16, %17, %18, %19, %20, %21, %22, %23, %24, %25, %26, %27, %28, %29, %30, %31}, "
    "da, db, p, 1, 1, 0, 0;}"
    : "=f"(d[0]), "=f"(d[1]), "=f"(d[2]), "=f"(d[3]), "=f"(d[4]), "=f"(d[5]), "=f"(d[6]), "=f"(d[7]),
      "=f"(d[8]), "=f"(d[9]), "=f"(d[10]), "=f"(d[11]), "=f"(d[12]), "=f"(d[13]), "=f"(d[14]), "=f"(d[15]),
      "=f"(d[16]), "=f"(d[17]), "=f"(d[18]), "=f"(d[19]), "=f"(d[20]), "=f"(d[21]), "=f"(d[22]), "=f"(d[23]),
      "=f"(d[24]), "=f"(d[25]), "=f"(d[26]), "=f"(d[27]), "=f"(d[28]), "=f"(d[29]), "=f"(d[30]), "=f"(d[31])
    : "r"(da), "r"(db));
}
__device__ __forceinline__ void wgmma_n96(float (&d)[48], uint32_t da, uint32_t db, int sd) {
  asm volatile("{.reg .pred p; .reg .b64 da, db; setp.ne.b32 p, %50, 0;\n"
    "mov.b64 da, {%48, 0x40000040}; mov.b64 db, {%49, 0x40000040};\n"
    "wgmma.mma_async.sync.aligned.m64n96k16.f32.bf16.bf16 "
    "{%0, %1, %2, %3, %4, %5, %6, %7, %8, %9, %10, %11, %12, %13, %14, %15, "
    "%16, %17, %18, %19, %20, %21, %22, %23, %24, %25, %26, %27, %28, %29, %30, %31, "
    "%32, %33, %34, %35, %36, %37, %38, %39, %40, %41, %42, %43, %44, %45, %46, %47}, "
    "da, db, p, 1, 1, 1, 0;}"
    : "+f"(d[0]), "+f"(d[1]), "+f"(d[2]), "+f"(d[3]), "+f"(d[4]), "+f"(d[5]), "+f"(d[6]), "+f"(d[7]),
      "+f"(d[8]), "+f"(d[9]), "+f"(d[10]), "+f"(d[11]), "+f"(d[12]), "+f"(d[13]), "+f"(d[14]), "+f"(d[15]),
      "+f"(d[16]), "+f"(d[17]), "+f"(d[18]), "+f"(d[19]), "+f"(d[20]), "+f"(d[21]), "+f"(d[22]), "+f"(d[23]),
      "+f"(d[24]), "+f"(d[25]), "+f"(d[26]), "+f"(d[27]), "+f"(d[28]), "+f"(d[29]), "+f"(d[30]), "+f"(d[31]),
      "+f"(d[32]), "+f"(d[33]), "+f"(d[34]), "+f"(d[35]), "+f"(d[36]), "+f"(d[37]), "+f"(d[38]), "+f"(d[39]),
      "+f"(d[40]), "+f"(d[41]), "+f"(d[42]), "+f"(d[43]), "+f"(d[44]), "+f"(d[45]), "+f"(d[46]), "+f"(d[47])
    : "r"(da), "r"(db), "r"(sd));
}
__device__ __forceinline__ void wgmma_n80(float (&d)[40], uint32_t da, uint32_t db, int sd) {
  asm volatile("{.reg .pred p; .reg .b64 da, db; setp.ne.b32 p, %42, 0;\n"
    "mov.b64 da, {%40, 0x40000040}; mov.b64 db, {%41, 0x40000040};\n"
    "wgmma.mma_async.sync.aligned.m64n80k16.f32.bf16.bf16 "
    "{%0, %1, %2, %3, %4, %5, %6, %7, %8, %9, %10, %11, %12, %13, %14, %15, "
    "%16, %17, %18, %19, %20, %21, %22, %23, %24, %25, %26, %27, %28, %29, %30, %31, "
    "%32, %33, %34, %35, %36, %37, %38, %39}, "
    "da, db, p, 1, 1, 1, 0;}"
    : "+f"(d[0]), "+f"(d[1]), "+f"(d[2]), "+f"(d[3]), "+f"(d[4]), "+f"(d[5]), "+f"(d[6]), "+f"(d[7]),
      "+f"(d[8]), "+f"(d[9]), "+f"(d[10]), "+f"(d[11]), "+f"(d[12]), "+f"(d[13]), "+f"(d[14]), "+f"(d[15]),
      "+f"(d[16]), "+f"(d[17]), "+f"(d[18]), "+f"(d[19]), "+f"(d[20]), "+f"(d[21]), "+f"(d[22]), "+f"(d[23]),
      "+f"(d[24]), "+f"(d[25]), "+f"(d[26]), "+f"(d[27]), "+f"(d[28]), "+f"(d[29]), "+f"(d[30]), "+f"(d[31]),
      "+f"(d[32]), "+f"(d[33]), "+f"(d[34]), "+f"(d[35]), "+f"(d[36]), "+f"(d[37]), "+f"(d[38]), "+f"(d[39])
    : "r"(da), "r"(db), "r"(sd));
}
__device__ __forceinline__ void wgmma_n64_kk(float (&d)[32], uint32_t da, uint32_t db, int sd) {
  asm volatile("{.reg .pred p; .reg .b64 da, db; setp.ne.b32 p, %34, 0;\n"
    "mov.b64 da, {%32, 0x40000040}; mov.b64 db, {%33, 0x40000040};\n"
    "wgmma.mma_async.sync.aligned.m64n64k16.f32.bf16.bf16 "
    "{%0, %1, %2, %3, %4, %5, %6, %7, %8, %9, %10, %11, %12, %13, %14, %15, "
    "%16, %17, %18, %19, %20, %21, %22, %23, %24, %25, %26, %27, %28, %29, %30, %31}, "
    "da, db, p, 1, 1, 0, 0;}"
    : "+f"(d[0]), "+f"(d[1]), "+f"(d[2]), "+f"(d[3]), "+f"(d[4]), "+f"(d[5]), "+f"(d[6]), "+f"(d[7]),
      "+f"(d[8]), "+f"(d[9]), "+f"(d[10]), "+f"(d[11]), "+f"(d[12]), "+f"(d[13]), "+f"(d[14]), "+f"(d[15]),
      "+f"(d[16]), "+f"(d[17]), "+f"(d[18]), "+f"(d[19]), "+f"(d[20]), "+f"(d[21]), "+f"(d[22]), "+f"(d[23]),
      "+f"(d[24]), "+f"(d[25]), "+f"(d[26]), "+f"(d[27]), "+f"(d[28]), "+f"(d[29]), "+f"(d[30]), "+f"(d[31])
    : "r"(da), "r"(db), "r"(sd));
}
__device__ __forceinline__ void wgmma_n64(float (&d)[32], uint32_t da, uint32_t db, int sd) {
  asm volatile("{.reg .pred p; .reg .b64 da, db; setp.ne.b32 p, %34, 0;\n"
    "mov.b64 da, {%32, 0x40000040}; mov.b64 db, {%33, 0x40000040};\n"
    "wgmma.mma_async.sync.aligned.m64n64k16.f32.bf16.bf16 "
    "{%0, %1, %2, %3, %4, %5, %6, %7, %8, %9, %10, %11, %12, %13, %14, %15, "
    "%16, %17, %18, %19, %20, %21, %22, %23, %24, %25, %26, %27, %28, %29, %30, %31}, "
    "da, db, p, 1, 1, 1, 0;}"
    : "+f"(d[0]), "+f"(d[1]), "+f"(d[2]), "+f"(d[3]), "+f"(d[4]), "+f"(d[5]), "+f"(d[6]), "+f"(d[7]),
      "+f"(d[8]), "+f"(d[9]), "+f"(d[10]), "+f"(d[11]), "+f"(d[12]), "+f"(d[13]), "+f"(d[14]), "+f"(d[15]),
      "+f"(d[16]), "+f"(d[17]), "+f"(d[18]), "+f"(d[19]), "+f"(d[20]), "+f"(d[21]), "+f"(d[22]), "+f"(d[23]),
      "+f"(d[24]), "+f"(d[25]), "+f"(d[26]), "+f"(d[27]), "+f"(d[28]), "+f"(d[29]), "+f"(d[30]), "+f"(d[31])
    : "r"(da), "r"(db), "r"(sd));
}

__device__ __forceinline__ void role1(int b, int& G, int& rb) {
  const int hi = b >= 66, c = b - 66 * hi;
  rb = c / 3; G = 3 * hi + (c - 3 * rb);
}
__device__ __forceinline__ void role2(int b, int& tb, int& cg) {
  tb = b / 5; cg = b - 5 * tb;
}
enum { T_KV = 0, T_QQ = 1, T_FFN = 2 };
__device__ __forceinline__ int step_info(int G, int s, int& i) {
  if (s < 2 && G < 5) { i = 2 * G + s; return T_KV; }
  if (s == 2 && G > 0) { i = 2 * (G - 1); return T_QQ; }
  i = s < 3 ? s : 3 + 6 * (s - 3) + G;
  return T_FFN;
}
__device__ __forceinline__ void step_src(const Params& p, int G, int s, const CUtensorMap*& m0, const CUtensorMap*& m1, int& c0, int& c1) {
  int i;
  const int ty = step_info(G, s, i);
  m0 = ty == T_FFN ? &p.w1 : &p.wqkv; m1 = ty == T_FFN ? &p.w3 : &p.wqkv;
  c0 = 64 * i + (ty == T_KV ? 640 : 0); c1 = c0 + (ty == T_KV ? 640 : (ty == T_QQ ? 64 : 0));
}

__host__ __device__ constexpr uint32_t p2_off(int slot) { return slot * ST2; }

__device__ __forceinline__ void wait_ready(uint32_t sb, uint32_t n) {
  uint32_t c = 0;
  while (lds_acq(sb + W_READY) < n) { if (++c > (SPIN_LIMIT << 4)) TRAP(0); }
}
__device__ __forceinline__ void p2_load(const CUtensorMap& mA, const CUtensorMap& mB, uint32_t dA, uint32_t fb, uint32_t wb, uint32_t wp,
                                        int ca, int rowb, int k0, uint32_t& cnext, uint32_t pace, int b, int i) {
  mbar_wait(wb, wp);
  expect_e(fb, ST2);
  while ((int)(clk32() - cnext) < 0) {}
  cnext += pace;
  tma_ld_e(dA + 16384, &mB, k0, rowb, fb);
  tma_ld3_e(dA, &mA, k0, ca, fb);
}

__device__ __forceinline__ void producer(const Params& p, uint32_t sb, int b, int lane) {
  int G, rb;
  role1(b, G, rb);
  const uint32_t gt0 = gtime32(), ck0 = clk32();
  uint32_t tmine = 0, ts[5];
  {
    const CUtensorMap *m0, *m1; int c0, c1;
    step_src(p, G, 0, m0, m1, c0, c1);
    if (elect_one()) {
      STAMP(48);
#pragma unroll
      for (int i = 0; i < I_EMPTY; i++) mbar_init(sb + MOFF + 8 * i, 1);
      fence_async_smem();
    }
    __syncwarp();
    bar_arrive(0, 384);
#pragma unroll 1
    for (int kt = 0; kt < 10; kt++) {
      if (kt < NS1) {
        expect_e(sb + B_FULL + 8 * kt, 16384);
        tma_ld_e(sb + WOFF + kt * 16384, m0, c0, kt * 64, sb + B_FULL + 8 * kt);
        tma_ld_e(sb + WOFF + kt * 16384 + 8192, m1, c1, kt * 64, sb + B_FULL + 8 * kt);
      }
      expect_e(sb + B_XFULL + 8 * kt, TB * 128);
      tma_ld_e(sb + XOFF + kt * XCH, &p.x1, kt * 64, rb * TB, sb + B_XFULL + 8 * kt);
    }
    if (elect_one()) STAMP(49);
    bar_sync(7, 128);
  }
#pragma unroll 1
  for (int s = 0; s < 7; s++) {
    const CUtensorMap *m0, *m1; int c0, c1;
    step_src(p, G, s, m0, m1, c0, c1);
    if (s == KVS_ + 1) {
      uint32_t c = 0;
      while (lds_acq(sb + W_KV) == 0) { if (++c > (SPIN_LIMIT << 4)) TRAP(0); }
      const int kcol = (b % 11) * 192, krow = min(b / 11, 10) * 60;
#pragma unroll 1
      for (int j = 0; j < 3; j++) {
        mbar_wait(sb + B_EMPTY + 8 * j, 1);
        expect_e(sb + B_FULL + 8 * j, 16384);
        tma_ld_e(sb + WOFF + j * 16384, &p.kva, kcol + 64 * j, krow, sb + B_FULL + 8 * j);
        tma_ld_e(sb + WOFF + j * 16384 + 8192, &p.vld, kcol + 64 * j, D_ + krow, sb + B_FULL + 8 * j);
        tma_ld_e(sb + WOFF + j * 16384 + 8192 + 60 * 128, &p.msk, kcol + 64 * j, 0, sb + B_FULL + 8 * j);
      }
    }
    if (s == 6) {
      const uint32_t g = __shfl_sync(0xffffffffu, gtime32(), 0);
      const float ns_per_clk = __fdividef((float)(g - gt0), (float)(clk32() - ck0));
      tmine = (g + (uint32_t)(T0_DELAY * ns_per_clk)) | 1u;
      tmine = __shfl_sync(0xffffffffu, tmine, 0);
      if (lane == 0) st_rlx(&p.sy->tslot[b], tmine);
    }
    const uint32_t rot = s > KVS_;
    const uint32_t dA = sb + WOFF + rot * (3 * 16384), dB = sb + WOFF - rot * (2 * 16384);
    const uint32_t fA = sb + B_FULL + rot * 24, fB = sb + B_FULL - rot * 16;
#pragma unroll 1
    for (uint32_t h = (s == 0); h < 2; h++) {
      const int k0 = h * 320;
      if (s == 6 && h == 1) {
#pragma unroll
        for (int q = 0; q < 5; q++) ts[q] = (q * 32 + lane < NCTA) ? ld_rlx(&p.sy->tslot[q * 32 + lane]) : tmine;
      }
#pragma unroll
      for (int j = 0; j < 5; j++) {
        const uint32_t fb = (j < 2 ? fA : fB) + 8 * j, dst = (j < 2 ? dA : dB) + j * 16384;
        mbar_wait(fb + (B_EMPTY - B_FULL), (j < 2 ? h : h ^ rot) ^ 1);
        expect_e(fb, 16384);
        tma_ld_e(dst, m0, c0, k0 + j * 64, fb);
        tma_ld_e(dst + 8192, m1, c1, k0 + j * 64, fb);
      }
    }
  }
  if (elect_one()) STAMP(40);
  if (b >= 130) return;
  int tb, cg;
  role2(b, tb, cg);
  const int rowb = tb * 80;
  uint32_t cnext;
  {
    uint32_t c = 0;
    while (__any_sync(0xffffffffu, (ts[0] == 0) | (ts[1] == 0) | (ts[2] == 0) | (ts[3] == 0) | (ts[4] == 0))) {
#pragma unroll
      for (int q = 0; q < 5; q++) ts[q] = (q * 32 + lane < NCTA) ? ld_rlx(&p.sy->tslot[q * 32 + lane]) : tmine;
      if (++c > SPIN_LIMIT) TRAP(0);
    }
    int d = 0;
#pragma unroll
    for (int q = 0; q < 5; q++) d = max(d, (int)(ts[q] - tmine));
    const uint32_t T0 = tmine + __reduce_max_sync(0xffffffffu, d);
    arrive_elect(sb + B_PD);
    wait_ready(sb, 15);
    while ((int)(gtime32() - T0) < 0) { if (++c > (SPIN_LIMIT << 4)) TRAP(0); }
    cnext = clk32() + T0_LEAD;
    if (elect_one()) STAMP(41);
  }
  uint32_t dA = sb, fb = sb + B_FULL2, par = 0;
  int k0 = 0;
#pragma unroll 1
  for (int i = 0; i < 7; i++) {
    p2_load(p.w2, p.hld, dA, fb, sb + (i < 2 ? B_DUMMY : B_T1), i < 2, 2 * cg, rowb, k0, cnext, PACE0, b, i);
    k0 += 64; dA += ST2; fb += 8;
  }
  dA = sb; fb = sb + B_FULL2;
#pragma unroll 1
  for (int kend = 14 * 64; kend <= 27 * 64; kend = (kend == 14 * 64 ? 15 * 64 : kend + 6 * 64)) {
#pragma unroll 1
    do {
      const uint32_t last = dA == sb + 7 * ST2;
      p2_load(p.w2, p.hld, dA, fb, fb + (B_EMPTY2 - B_FULL2), par ^ last, 2 * cg, rowb, k0, cnext, PACE, b, k0 >> 6);
      k0 += 64; dA += ST2; fb += 8;
      if (last) { dA = sb; fb = sb + B_FULL2; par ^= 1; }
    } while (k0 != kend);
    if (kend == 14 * 64) mbar_wait(sb + B_S7, 0);
    else wait_ready(sb, kend == 27 * 64 ? NK2 : (kend >> 6) + 6);
  }
#pragma unroll 1
  for (k0 = 0; k0 < D_; k0 += 64) {
    const uint32_t last = dA == sb + 7 * ST2;
    p2_load(p.mm, p.ald, dA, fb, fb + (B_EMPTY2 - B_FULL2), par ^ last, 2 * cg, rowb, k0, cnext, PACE2, b, 27 + (k0 >> 6));
    dA += ST2; fb += 8;
    if (last) { dA = sb; fb = sb + B_FULL2; par ^= 1; }
  }
  mbar_wait(sb + B_EMPTY2 + 8 * 6, 1);
  expect_e(sb + B_XRES, 2 * 80 * 128);
  tma_ld_e(sb + XROFF, &p.xres, cg * 128, rowb, sb + B_XRES);
  tma_ld_e(sb + XROFF + XCH, &p.xres, cg * 128 + 64, rowb, sb + B_XRES);
  if (elect_one()) STAMP(42);
}

struct Watch {
  const unsigned *f0, *f1;
  unsigned t0v, t1v, published;
  __device__ __forceinline__ Watch(Sync* sy, int b, int lane) {
    int tb, cg;
    role2(min(b, 129), tb, cg);
    t0v = 1; t1v = 1; published = b < 130 ? 0 : NK2;
    if (lane < 27) { f0 = &sy->hflag[(tb * 80) / TB * 32 + lane]; f1 = &sy->hflag[min(tb * 80 + 79, S_ - 1) / TB * 32 + lane]; }
    else { f0 = &sy->c_m[0]; f1 = &sy->c_a[tb]; t0v = NMC; t1v = (tb == 25) ? 3 : 5; }
  }
  __device__ __forceinline__ void check(unsigned v0, unsigned v1, uint32_t sb, int lane) {
    const unsigned m = __ballot_sync(0xffffffffu, (v0 >= t0v) & (v1 >= t1v));
    unsigned n = __ffs(~m | 0x10000000u) - 1;
    if (n == 28) n = NK2;
    if (n > published) {
      published = n;
      fence_acq();
      __syncwarp();
      if (lane == 0) {
        asm volatile("red.release.cta.shared::cta.max.u32 [%0], %1;" ::"r"(sb + W_READY), "r"(n) : "memory");
      }
    }
  }
};

__device__ __forceinline__ void agent(const Params& p, uint32_t sb, int b, int lane) {
  Sync* sy = p.sy;
  int G, rb;
  role1(b, G, rb);
  const CUtensorMap *n0, *n1; int d0, d1;
  step_src(p, G, min(lane + 1, 6), n0, n1, d0, d1);
  if (rb >= 10) { n0 = n1; d0 = d1; }
  d1 = (rb < 10 ? rb : rb - 10) * 64;
  if (lane < 19) desc_pf(&p.x1 + lane);
  mbar_wait(sb + B_XFULL + 8 * 6, 0);
  if (rb < 20 && lane == 0) tma_pf(n0, d0, d1);
  mbar_wait(sb + B_XFULL + 8 * 9, 0);
  if (rb < 20 && lane == 1) tma_pf(n0, d0, d1);
  Watch w(sy, b, lane);
  int s = 0, n1s = 0;
  uint32_t todo = b < NMC ? 3u : 0u, c = 0;
#pragma unroll 1
  while (s < 7 || todo != 0 || w.published < 21) {
    unsigned v0 = 0, v1 = 0;
    const bool look = s >= 4 && w.published < 21;
    if (look) { v0 = ld_rlx(w.f0); v1 = ld_rlx(w.f1); }
    int ix;
    const int ty = step_info(G, min(s, 6), ix);
    const int ca = rb * 96 + (rb & 1) * 32, cb = rb * 96 + 64 - (rb & 1) * 64;
    if (ty != T_FFN) {
      mbar_wait(sb + B_S1F, n1s & 1);
      n1s++;
      if (lane == 0) {
        if (ty == T_QQ) tma_st(&p.pqst, 64 * ix + 64, rb * TB, sb + SOFF + XCH);
        else { tma_st(&p.kva, ca, D_ + 64 * ix, sb + SOFF + XCH); tma_st(&p.kvb, cb, D_ + 64 * ix, sb + SOFF + XCH + 8192); }
        bulk_commit();
        bulk_wait_all();
        mbar_arrive(sb + B_S1E);
      }
      __syncwarp();
      mbar_wait(sb + B_STGF + 8 * (s & 1), (s >> 1) & 1);
    }
    if (s < 7 && (s < 4 ? mbar_try(sb + B_STGF + 8 * (s & 1), (s >> 1) & 1) : mbar_test(sb + B_STGF + 8 * (s & 1), (s >> 1) & 1))) {
      if (lane == 0) {
        if (ty == T_FFN) tma_st(&p.hst, 64 * ix, rb * TB, sb + SOFF);
        else if (ty == T_QQ) tma_st(&p.pqst, 64 * ix, rb * TB, sb + SOFF);
        else { tma_st(&p.kva, ca, 64 * ix, sb + SOFF); tma_st(&p.kvb, cb, 64 * ix, sb + SOFF + 8192); }
        bulk_commit();
        bulk_wait_all();
        mbar_arrive(sb + B_STG + 8 * (s & 1));
        if (s == 6) mbar_arrive(sb + B_S7);
        red_rlx(ty == T_FFN ? &sy->hflag[rb * 32 + ix] : (ty == T_QQ ? &sy->c_q[0] : &sy->c_kv[0]), 1);
        STAMP(50 + s);
        if (s == 0 && b < 128) {
          bulk_pf(reinterpret_cast<const char*>(p.wo) + b * 6400, 6400);
          bulk_pf(reinterpret_cast<const char*>(p.w2p) + b * 17280, 17280);
        }
      }
      if (rb < 20 && lane == s + 2 && s < 4) tma_pf(n0, d0, d1);
      __syncwarp();
      s++;
    }
    if (s >= 5) {
      if ((todo & 1) && mbar_test(sb + B_T6, 0) && lds_acq(sb + W_B) != 0) {
        todo &= ~1u;
        expect_e(sb + B_WO, 16384);
        tma_ld_e(sb + WOOFF, &p.wom, (b % 10) * 64, (b / 10) * 60, sb + B_WO);
        tma_ld_e(sb + WOOFF + 8192, &p.bld, 0, (b / 10) * 64, sb + B_WO);
      }
      if ((todo & 2) && mbar_test(sb + B_MF, 0)) {
        todo &= ~2u;
        if (lane == 0) {
          tma_st(&p.mst, (b % 10) * 64, (b / 10) * 60, sb + WOOFF + 8192);
          bulk_commit();
          bulk_wait_all();
          mbar_arrive(sb + B_S7);
          red_rlx(&sy->c_m[0], 1);
          STAMP(45);
        }
        __syncwarp();
      }
    }
    if (look) w.check(v0, v1, sb, lane);
    if (s >= 4) __nanosleep(50);
    if (++c > SPIN_LIMIT) TRAP(s);
  }
  if (b < 130) mbar_wait(sb + B_PD, 0);
  bar_sync(6, 96);
  unsigned last = 0;
  if (lane == 0) { __threadfence(); last = atomicAdd(&sy->c_done[0], 1) == NCTA - 1; }
  if (__shfl_sync(0xffffffffu, last, 0)) {
    __threadfence();
    uint4* w = reinterpret_cast<uint4*>(sy);
#pragma unroll 1
    for (int i = lane; i < (int)(sizeof(Sync) / 16); i += 32) w[i] = make_uint4(0, 0, 0, 0);
  }
}

__device__ __forceinline__ void aux(const Params& p, uint32_t sb, int b, int aw, int lane) {
  Sync* sy = p.sy;
  char* rows = reinterpret_cast<char*>(p.pq_p + (size_t)16 * b * D_);
  const uint32_t abuf = sb + SOFF + XCH;
  if (b == 0) {
#pragma unroll 1
    for (int i = aw * 32 + lane; i < KTP / 8; i += 64) {
      const int rb = i / 12, q = i - 12 * rb;
      const int left = min(TB, S_ - rb * TB) - 8 * ((rb & 1) ? (q < 4 ? q + 8 : q - 4) : q);
      reinterpret_cast<uint4*>(p.mask_p)[i] =
          make_uint4(left > 0 ? 0x3F803F80u : 0u, left > 2 ? 0x3F803F80u : 0u, left > 4 ? 0x3F803F80u : 0u, left > 6 ? 0x3F803F80u : 0u);
    }
    __syncwarp();
    if (lane == 0) red_rel(&sy->c_kv[0], 1);
  }
  if (aw == 0) {
    int G, rb;
    role1(b, G, rb);
    const unsigned long long* src = &sy->stats[rb * 96 + lane];
    unsigned long long v0, v1, v2;
    uint32_t c = 0;
    do {
      v0 = ld_rlx64(src); v1 = ld_rlx64(src + 32); v2 = ld_rlx64(src + 64);
      if (++c > SPIN_LIMIT) TRAP(0);
    } while (v0 == 0 || v1 == 0 || v2 == 0);
    sts64v(sb + STATS + 8 * lane, v0); sts64v(sb + STATS + 256 + 8 * lane, v1); sts64v(sb + STATS + 512 + 8 * lane, v2);
    mbar_arrive(sb + B_STATS);
    __syncwarp();
    wait_count(&sy->c_kv[0], 10 * NRB + 2);
    if (lane == 0) { fence_async_global(); sts_rel(sb + W_KV, 1); STAMP(44); }
    if (b < NKVC) {
      mbar_wait(sb + B_KVF, 0);
      if (lane == 0) {
        const int hg = b / 11, part = b - 11 * hg, nh = hg == 10 ? 2 : 3;
#pragma unroll 1
        for (int hl = 0; hl < nh; hl++) bulk_st(p.kvp + ((3 * hg + hl) * 11 + part) * 400, abuf + 1600 * hl, 1600);
        bulk_st(p.zp + part * D_ + 60 * hg, abuf + 4800, 80 * nh);
        bulk_commit();
        bulk_wait_all();
        red_rlx(&sy->c_p[0], 1);
      }
      __syncwarp();
    }
    if (b < 128) {
      wait_count(&sy->c_q[0], 5 * NRB);
      if (lane == 0) { fence_async_global(); mbar_expect_tx(sb + B_AL, 10240); bulk_ld(abuf, rows, 10240, sb + B_AL); }
      sts128(sb + ZS + 16 * lane, make_uint4(0, 0, 0, 0));
      if (lane < 8) sts128(sb + ZS + 512 + 16 * lane, make_uint4(0, 0, 0, 0));
      const int u = 25 * b + lane, head = u / 100, r = u - 100 * head, zu = 2 * b + lane - 25;
      const int hg = head / 3, hl = head - 3 * hg;
      const bool isz = lane >= 25, act = lane < 25 || (lane < 27 && zu < D_ / 4);
      const float4* src = isz ? reinterpret_cast<const float4*>(p.zp) + zu : reinterpret_cast<const float4*>(p.kvp + head * 11 * 400) + r;
      uint32_t sdst = isz ? sb + ZS + 640 + 16 * (lane - 25) : sb + ZS + 128 * (lane / 5) + 40 * hl + 8 * (lane % 5);
      __nv_bfloat16* gdst = p.b_p + (64 * hg + 20 * hl + r / 5) * 64;
      asm volatile("" : "+l"(src), "+r"(sdst), "+l"(gdst));
      wait_count(&sy->c_p[0], NKVC);
      if (lane == 0) STAMP(43);
      if (act) {
        const int stride = isz ? D_ / 4 : 100;
        float4 s = make_float4(0.f, 0.f, 0.f, 0.f);
#pragma unroll
        for (int q = 0; q < 11; q++) {
          const float4 v = __ldcg(src + q * stride);
          s.x += v.x; s.y += v.y; s.z += v.z; s.w += v.w;
        }
        if (isz) sts128(sdst, make_uint4(__float_as_uint(s.x), __float_as_uint(s.y), __float_as_uint(s.z), __float_as_uint(s.w)));
        else
          asm volatile("st.shared.v2.u32 [%0], {%1,%2};" ::"r"(sdst),
                       "r"(pack2(s.x * LN2, s.y * LN2)), "r"(pack2(s.z * LN2, s.w * LN2)) : "memory");
      }
      fence_async_smem();
      __syncwarp();
      if (lane == 0) {
        bulk_st(gdst, sb + ZS, 640);
        if (b < 80) bulk_st(p.z + 8 * b, sb + ZS + 640, 32);
        bulk_commit();
        bulk_wait_all();
        red_rlx(&sy->c_b[0], 1);
      }
      __syncwarp();
    }
  }
  if (b < 128) {
    if (aw == 1) {
      wait_count(&sy->c_b[0], 128);
      if (lane == 0) {
        fence_async_global();
        sts_rel(sb + W_B, 1);
        mbar_expect_tx(sb + B_Z, 2560);
        bulk_ld(sb + ZS, p.z, 2560, sb + B_Z);
        STAMP(46);
      }
    }
    mbar_wait(sb + B_Z, 0);
    float z[20];
#pragma unroll
    for (int i = 0; i < 5; i++) {
      const float4 t = lds128f(sb + ZS + 80 * lane + 16 * i);
      z[4 * i] = t.x; z[4 * i + 1] = t.y; z[4 * i + 2] = t.z; z[4 * i + 3] = t.w;
    }
#pragma unroll 1
    for (int r = 0; r < 2; r++) {
      mbar_wait(sb + B_AL, r);
#pragma unroll 1
      for (int t0 = 0; t0 < 4; t0 += 2) {
        const uint32_t a = abuf + (4 * aw + t0) * 1280 + 40 * lane;
        uint2 v[2][5];
#pragma unroll
        for (int tk = 0; tk < 2; tk++)
#pragma unroll
          for (int i = 0; i < 5; i++) asm volatile("ld.shared.v2.u32 {%0,%1}, [%2];" : "=r"(v[tk][i].x), "=r"(v[tk][i].y) : "r"(a + tk * 1280 + 8 * i) : "memory");
        float inv[2];
#pragma unroll
        for (int tk = 0; tk < 2; tk++) {
          float den = 1e-6f, den2 = 0.f;
#pragma unroll
          for (int i = 0; i < 5; i++) {
            den = fmaf(bf_lo(v[tk][i].x), z[4 * i], den); den2 = fmaf(bf_hi(v[tk][i].x), z[4 * i + 1], den2);
            den = fmaf(bf_lo(v[tk][i].y), z[4 * i + 2], den); den2 = fmaf(bf_hi(v[tk][i].y), z[4 * i + 3], den2);
          }
          inv[tk] = rcp(den + den2);
        }
#pragma unroll
        for (int tk = 0; tk < 2; tk++)
#pragma unroll
          for (int i = 0; i < 5; i++)
            asm volatile("st.shared.v2.u32 [%0], {%1,%2};" ::"r"(a + tk * 1280 + 8 * i),
                         "r"(pack2(bf_lo(v[tk][i].x) * inv[tk], bf_hi(v[tk][i].x) * inv[tk])),
                         "r"(pack2(bf_lo(v[tk][i].y) * inv[tk], bf_hi(v[tk][i].y) * inv[tk])) : "memory");
      }
      fence_async_smem();
      bar_sync(5, 64);
      if (aw == 0 && lane == 0) {
        bulk_st(rows + r * 10240, abuf, 10240);
        bulk_commit();
        bulk_wait_all();
        if (r == 0) { mbar_expect_tx(sb + B_AL, 10240); bulk_ld(abuf, rows + 10240, 10240, sb + B_AL); }
        else { red_rlx(&sy->c_a[b / 5], 1); STAMP(47); }
      }
      __syncwarp();
    }
  }
  if (aw == 1) {
    Watch w(sy, b, lane);
    uint32_t c = 0;
#pragma unroll 1
    while (w.published < NK2) {
      w.check(ld_rlx(w.f0), ld_rlx(w.f1), sb, lane);
      if (++c > SPIN_LIMIT) TRAP(0);
    }
  }
  bar_arrive(6, 96);
}

__device__ __forceinline__ void ln_stats(uint32_t sb, int tid, int G, int rb, Sync* sy) {
  const int tok = 16 * G + (tid >> 3);
  uint32_t a = sb + XOFF + tok * 128;
  mbar_wait(sb + B_XFULL, 0);
  uint32_t p0;
  asm volatile("ld.shared.u32 %0, [%1];" : "=r"(p0) : "r"(a) : "memory");
  const float piv = bf_lo(p0);
  float s4[4] = {0.f, 0.f, 0.f, 0.f}, q4[4] = {0.f, 0.f, 0.f, 0.f};
  a += (tid & 7) * 16;
#pragma unroll 1
  for (int c = 0; c < 10; c += 2) {
    mbar_wait(sb + B_XFULL + 8 * c + 8, 0);
    mbar_wait(sb + B_XFULL + 8 * c, 0);
    const uint4 v = lds128(a + c * XCH), u = lds128(a + c * XCH + XCH);
    const uint32_t w[8] = {v.x, v.y, v.z, v.w, u.x, u.y, u.z, u.w};
#pragma unroll
    for (int q = 0; q < 8; q++) {
      const float d0 = bf_lo(w[q]) - piv, d1 = bf_hi(w[q]) - piv;
      s4[q & 3] += d0 + d1;
      q4[q & 3] = fmaf(d0, d0, fmaf(d1, d1, q4[q & 3]));
    }
  }
  float sm = (s4[0] + s4[1]) + (s4[2] + s4[3]), sq = (q4[0] + q4[1]) + (q4[2] + q4[3]);
#pragma unroll
  for (int o = 1; o < 8; o <<= 1) { sm += __shfl_xor_sync(0xffffffffu, sm, o); sq += __shfl_xor_sync(0xffffffffu, sq, o); }
  if ((tid & 7) == 0) {
    const float dm = sm * (1.f / D_);
    const float var = fmaxf(sq * (1.f / D_) - dm * dm, 0.f);
    uint32_t rl = __float_as_uint(rsqrtf(var + 1e-5f) * LOG2E);
    if (tok >= min(TB, S_ - rb * TB) || rl == 0) rl = 0x80000000u;
    st_rlx64(&sy->stats[rb * 96 + tok], ((unsigned long long)rl << 32) | __float_as_uint(-(piv + dm)));
  }
}

__device__ __forceinline__ void load_stats(float (&st)[48], uint32_t sb, int lane) {
  mbar_wait(sb + B_STATS, 0);
#pragma unroll
  for (int j = 0; j < 12; j++) {
    const float4 v = lds128f(sb + STATS + 16 * (lane & 3) + 64 * j);
    st[4 * j] = v.x; st[4 * j + 1] = v.y; st[4 * j + 2] = v.z; st[4 * j + 3] = v.w;
  }
}
__device__ __forceinline__ void chain(float& v, uint32_t after, uint32_t zero) {
  v = __uint_as_float(__float_as_uint(v) | (after & zero));
}
__device__ __forceinline__ uint32_t token(uint32_t a) { uint32_t v; asm volatile("ld.volatile.shared::cta.u32 %0, [%1];" : "=r"(v) : "r"(a) : "memory"); return v; }
__device__ __forceinline__ void link(float& v, uint32_t tok) { v = __uint_as_float(__float_as_uint(v) | tok); }
template <bool PHI, bool TRANS>
__device__ __forceinline__ void epi_attn(const float (&a)[48], const float (&st)[48], int lane, uint32_t zero, uint32_t zaddr,
                                         uint32_t dst, uint32_t dst2) {
  float c0 = __shfl_sync(0xffffffffu, a[44], lane | 3), c1 = __shfl_sync(0xffffffffu, a[46], lane | 3);
  uint32_t plo = 0, phi_ = 0, tok = 0;
#pragma unroll
  for (int j = 0; j < 12; j++) {
    float y[4];
#pragma unroll
    for (int q = 0; q < 4; q++) {
      const float yl = fmaf(st[4 * j + 2 * (q & 1)], q < 2 ? c0 : c1, a[4 * j + q]) * st[4 * j + 2 * (q & 1) + 1];
      y[q] = PHI ? phi_l(yl) : yl;
    }
    const uint32_t lo = pack2(y[0], y[1]), hi = pack2(y[2], y[3]);
    if ((j + 1) % 2 == 0 && j < 11) { chain(c0, lo, zero); chain(c1, hi, zero); }
    if (j >= 2 && (j & 1) && j < 11) link(c0, tok);
    if (j & 1) {
      if (TRANS) stsm4t(dst + (j - 1) * 1024, plo, phi_, lo, hi);
      else stsm4((j < 8 ? dst : dst2) ^ (((j - 1) & 7) << 4), plo, phi_, lo, hi);
      if (j < 9) tok = token(zaddr);
    }
    plo = lo; phi_ = hi;
  }
}
template <int SLOT>
__device__ __forceinline__ void p2_tile(float (&acc)[40], uint32_t sb, uint32_t wgo, uint32_t par, uint32_t npar, uint32_t eb, int sd, bool& ok) {
  if (!ok) mbar_wait(sb + B_FULL2 + 8 * SLOT, par);
  ok = mbar_test(sb + B_FULL2 + 8 * ((SLOT + 1) % NS2), npar);
  wg_fence();
#pragma unroll
  for (int kk = 0; kk < 4; kk++) wgmma_n80(acc, dlo(p2_off(SLOT)) + wgo + kk * 128, dlo(p2_off(SLOT) + 16384) + kk * 2, kk ? 1 : sd);
  wg_commit();
  wg_wait<1>();
  arrive_elect(eb);
}
__device__ __forceinline__ void epi_ffn(const float (&a)[48], const float (&u)[48], const float (&st)[48], int lane, uint32_t zero,
                                        uint32_t stg_lane) {
  float cg0 = __shfl_sync(0xffffffffu, a[44], lane | 3), cg1 = __shfl_sync(0xffffffffu, a[46], lane | 3);
  const float cu0 = __shfl_sync(0xffffffffu, u[44], lane | 3), cu1 = __shfl_sync(0xffffffffu, u[46], lane | 3);
  uint32_t plo = 0, phi_ = 0;
#pragma unroll
  for (int j = 0; j < 12; j++) {
    float h[4];
#pragma unroll
    for (int q = 0; q < 4; q++) {
      const float nm = st[4 * j + 2 * (q & 1)], rl = st[4 * j + 2 * (q & 1) + 1];
      const float gl = fmaf(nm, q < 2 ? cg0 : cg1, a[4 * j + q]) * rl;
      const float du = fmaf(nm, q < 2 ? cu0 : cu1, u[4 * j + q]);
      h[q] = (gl * du) * (rl * rcp(fmaf(ex2(-gl), LOG2E * LOG2E, LOG2E * LOG2E)));
    }
    const uint32_t lo = pack2(h[0], h[1]), hi = pack2(h[2], h[3]);
    if (j & 1) stsm4t(stg_lane + (j - 1) * 1024, plo, phi_, lo, hi);
    if (j < 11) { chain(cg0, lo, zero); chain(cg1, hi, zero); }
    plo = lo; phi_ = hi;
  }
}

__device__ __forceinline__ void consumer(const Params& p, uint32_t sb, int b, int wg, int tid) {
  int G, rb;
  role1(b, G, rb);
  const int lane = tid & 31, wq = tid >> 5;
  const int mi = lane >> 3, r8 = lane & 7;
  uint32_t stg_lane = sb + SOFF + (8 * (mi >> 1) + r8) * 128 + (((2 * wq + (mi & 1)) ^ r8) << 4);
  asm volatile("mov.u32 %0, %0;" : "+r"(stg_lane));
  const uint32_t zero = p.zero;
  if (wg == 1) ln_stats(sb, tid, G, rb, p.sy);
  {
    float a0[48], a1[48], st[48];
#pragma unroll 1
    for (int s = wg; s < 7; s += 2) {
      float kv[32];
      const uint32_t rot = s > KVS_;
      const uint32_t alA = dlo(WOFF) + rot * (3 * 1024), alB = dlo(WOFF) - rot * (2 * 1024);
      const uint32_t fbA = sb + B_FULL + rot * 24, fbB = sb + B_FULL - rot * 16;
      uint32_t eb = sb + B_DUMMY;
      if (s > 0) bar_sync(1 + wg, 256);
      if (tid == 0) STAMP(3 * s);
      {
        if (s == 0) mbar_wait(sb + B_XFULL, 0);
        mbar_wait(fbA, 0);
        wg_fence();
        wgmma_n96_first(a0, alA, dlo(XOFF));
        wgmma_n96_first(a1, alA + 512, dlo(XOFF));
#pragma unroll
        for (int kk = 1; kk < 4; kk++) {
          wgmma_n96(a0, alA + kk * 128, dlo(XOFF) + kk * 2, 1);
          wgmma_n96(a1, alA + 512 + kk * 128, dlo(XOFF) + kk * 2, 1);
        }
        wg_commit();
        eb = fbA + (B_EMPTY - B_FULL);
      }
#pragma unroll 1
      for (uint32_t h = 0; h < 2; h++) {
        const uint32_t blo = dlo(XOFF) + h * (5 * XCH >> 4);
#pragma unroll
        for (int j = 0; j < 5; j++) {
          const uint32_t alo = (j < 2 ? alA : alB) + j * 1024, fb = (j < 2 ? fbA : fbB) + 8 * j;
          if (j == 0 && h == 0) continue;
          if (s == 0) mbar_wait(sb + B_XFULL + 40 * h + 8 * j, 0);
          mbar_wait(fb, j < 2 ? h : h ^ rot);
          wg_fence();
#pragma unroll
          for (int kk = 0; kk < 4; kk++) {
            wgmma_n96(a0, alo + kk * 128, blo + j * (XCH >> 4) + kk * 2, 1);
            wgmma_n96(a1, alo + 512 + kk * 128, blo + j * (XCH >> 4) + kk * 2, 1);
          }
          wg_commit();
          wg_wait<1>();
          arrive_elect(eb);
          eb = fb + (B_EMPTY - B_FULL);
          if (j == 2 && h == 1 && s == 6) arrive_elect(sb + B_T6);
        }
      }
      if (s == KVS_) {
#pragma unroll
        for (int j = 0; j < 3; j++) {
          mbar_wait(sb + B_FULL + 8 * j, 0);
          wg_fence();
#pragma unroll
          for (int kk = 0; kk < 4; kk++) {
            if (j == 0 && kk == 0) wgmma_n64_kk_first(kv, dlo(WOFF), dlo(WOFF) + 512);
            else wgmma_n64_kk(kv, dlo(WOFF) + j * 1024 + kk * 2, dlo(WOFF) + j * 1024 + 512 + kk * 2, 1);
          }
          wg_commit();
        }
        bar_arrive(2 - wg, 256);
        wg_wait<3>(); arrive_elect(eb);
        wg_wait<2>(); arrive_elect(sb + B_EMPTY);
        wg_wait<1>(); arrive_elect(sb + B_EMPTY + 8);
        eb = sb + B_EMPTY + 16;
      } else if (s < 6) bar_arrive(2 - wg, 256);
      if (s < 2) load_stats(st, sb, lane);
      wg_wait<0>();
      keep(a0); keep(a1);
      arrive_elect(eb);
      if (s == 6) arrive_elect(sb + B_T1);
      if (tid == 0) STAMP(3 * s + 1);
      int ix;
      const int ty = step_info(G, s, ix);
      if (s > 0) mbar_wait(ty == T_KV ? sb + B_S1E : sb + B_STG + 8 * (1 - wg), ((s - 1) >> 1) & 1);
      if (s == KVS_ && b < NKVC) {
        keep(kv);
#pragma unroll
        for (int hf = 0; hf < 2; hf++) {
          const int r = 16 * wq + (lane >> 2) + 8 * hf, hl = r / 20;
          if (hl < 3) {
            const uint32_t dst = sb + SOFF + XCH + 80 * r - 80 * hl + 8 * (lane & 3);
#pragma unroll
            for (int j = 0; j < 8; j++)
              if ((unsigned)(8 * j + 2 * (lane & 3) - 20 * hl) < 20u)
                asm volatile("st.shared.v2.f32 [%0], {%1,%2};" ::"r"(dst + 32 * j), "f"(kv[4 * j + 2 * hf]), "f"(kv[4 * j + 2 * hf + 1]) : "memory");
            if ((lane & 3) == 2) asm volatile("st.shared.f32 [%0], %1;" ::"r"(sb + SOFF + XCH + 4800 + 4 * r), "f"(kv[28 + 2 * hf]) : "memory");
          }
        }
        fence_async_smem();
        mbar_arrive(sb + B_KVF);
      }
      if (ty == T_KV) {
        const uint32_t row = 16 * wq + 8 * (mi & 1) + r8;
        const uint32_t dA = sb + SOFF + row * 128 + (((mi >> 1) ^ r8) << 4), dB = sb + SOFF + 8192 + row * 64 + (((mi >> 1) ^ (r8 >> 1)) << 4);
        epi_attn<false, false>(a1, st, lane, zero, sb + W_ZERO, dA + XCH, dB + XCH);
        fence_async_smem();
        mbar_arrive(sb + B_S1F);
        if (s > 0) mbar_wait(sb + B_STG, 0);
        epi_attn<true, false>(a0, st, lane, zero, sb + W_ZERO, dA, dB);
      } else if (ty == T_QQ) {
        epi_attn<true, true>(a1, st, lane, zero, sb + W_ZERO, stg_lane + XCH, 0);
        fence_async_smem();
        mbar_arrive(sb + B_S1F);
        epi_attn<true, true>(a0, st, lane, zero, sb + W_ZERO, stg_lane, 0);
      } else epi_ffn(a0, a1, st, lane, zero, stg_lane);
      fence_async_smem();
      mbar_arrive(sb + B_STGF + 8 * wg);
      if (tid == 0) STAMP(3 * s + 2);
    }
    if (b >= 130) return;
  }
  int tb, cg;
  role2(b, tb, cg);
  float o[40], sa[40], gt[40];
  const bool do_m = wg == 1 && b < NMC;
  const uint32_t wgo = wg * 512;
  if (tid == 0) STAMP(24 + 4 * wg);
#define P2S(n)
#define EMP(j) (sb + B_EMPTY2 + 8 * (j))
  if (do_m) {
    float m[32];
    mbar_wait(sb + B_WO, 0);
    wg_fence();
#pragma unroll
    for (int kk = 0; kk < 4; kk++) wgmma_n64(m, dlo(WOOFF) + kk * 128, dlo(WOOFF + 8192) + kk * 2, kk);
    wg_commit();
    wg_wait<0>();
    keep(m);
    bar_sync(4, 128);
#pragma unroll
    for (int j = 0; j < 4; j++)
      stsm4t(stg_lane - (SOFF - WOOFF - 8192) + j * 2048, pack2(m[8 * j], m[8 * j + 1]), pack2(m[8 * j + 2], m[8 * j + 3]),
             pack2(m[8 * j + 4], m[8 * j + 5]), pack2(m[8 * j + 6], m[8 * j + 7]));
    fence_async_smem();
    mbar_arrive(sb + B_MF);
  }
  bool ok = false;
#pragma unroll 1
  for (uint32_t r = 0; r < 4; r++) {
    const uint32_t par = r & 1;
    p2_tile<0>(o, sb, wgo, par, par, r == 0 ? sb + B_DUMMY : (r == 1 ? EMP(6) : EMP(7)), r, ok); P2S((r ? 8 * r - 1 : 0))
    p2_tile<1>(o, sb, wgo, par, par, EMP(0), 1, ok); P2S((r ? 8 * r - 1 : 0) + 1)
    p2_tile<2>(o, sb, wgo, par, par, EMP(1), 1, ok); P2S((r ? 8 * r - 1 : 0) + 2)
    p2_tile<3>(o, sb, wgo, par, par, EMP(2), 1, ok); P2S((r ? 8 * r - 1 : 0) + 3)
    if (r == 3) break;
    p2_tile<4>(o, sb, wgo, par, par, EMP(3), 1, ok); P2S((r ? 8 * r - 1 : 0) + 4)
    p2_tile<5>(o, sb, wgo, par, par, EMP(4), 1, ok); P2S((r ? 8 * r - 1 : 0) + 5)
    p2_tile<6>(o, sb, wgo, par, par ^ 1, EMP(5), 1, ok); P2S((r ? 8 * r - 1 : 0) + 6)
    if (r == 0) { ok = false; continue; }
    p2_tile<7>(o, sb, wgo, par ^ 1, par ^ 1, EMP(6), 1, ok); P2S((r ? 8 * r - 1 : 0) + 7)
  }
#define SILU(n)                                                                                    \
  _Pragma("unroll") for (int q = 0; q < 5; q++) {                                                  \
    if ((n) >= 2) gt[5 * ((n) - 2) + q] *= o[5 * ((n) - 2) + q];                                   \
    if ((n) >= 1 && (n) < 9) gt[5 * ((n) - 1) + q] = rcp(1.f + gt[5 * ((n) - 1) + q]);             \
    if ((n) < 8) gt[5 * (n) + q] = ex2(o[5 * (n) + q] * -LOG2E);                                   \
  }
  p2_tile<4>(sa, sb, wgo, 1, 1, EMP(3), 0, ok); keep(o); P2S(27) SILU(0)
  p2_tile<5>(sa, sb, wgo, 1, 1, EMP(4), 1, ok); P2S(28) SILU(1)
  p2_tile<6>(sa, sb, wgo, 1, 0, EMP(5), 1, ok); P2S(29) SILU(2)
  p2_tile<7>(sa, sb, wgo, 0, 0, EMP(6), 1, ok); P2S(30) SILU(3)
  p2_tile<0>(sa, sb, wgo, 0, 0, sb + B_DUMMY, 1, ok); P2S(31) SILU(4)
  p2_tile<1>(sa, sb, wgo, 0, 0, sb + B_DUMMY, 1, ok); P2S(32) SILU(5)
  p2_tile<2>(sa, sb, wgo, 0, 0, sb + B_DUMMY, 1, ok); P2S(33) SILU(6)
  p2_tile<3>(sa, sb, wgo, 0, 0, sb + B_DUMMY, 1, ok); P2S(34) SILU(7)
  p2_tile<4>(sa, sb, wgo, 0, 0, sb + B_DUMMY, 1, ok); P2S(35) SILU(8)
  p2_tile<5>(sa, sb, wgo, 0, 0, sb + B_DUMMY, 1, ok); P2S(36) SILU(9)
  uint32_t xr[20];
  mbar_wait(sb + B_XRES, 0);
  const uint32_t ob = stg_lane - (SOFF - XROFF) + wg * XCH;
#pragma unroll
  for (int j = 0; j < 5; j++) ldsm4t(ob + j * 2048, xr[4 * j], xr[4 * j + 1], xr[4 * j + 2], xr[4 * j + 3]);
  wg_wait<0>();
  keep(sa);
  if (tid == 0) STAMP(26 + 4 * wg);
#pragma unroll
  for (int j = 0; j < 5; j++) {
    uint32_t r[4];
#pragma unroll
    for (int q = 0; q < 4; q++) {
      const int e = 8 * j + 2 * q;
      r[q] = pack2(fmaf(sa[e], gt[e], bf_lo(xr[4 * j + q])), fmaf(sa[e + 1], gt[e + 1], bf_hi(xr[4 * j + q])));
    }
    stsm4t(ob + j * 2048, r[0], r[1], r[2], r[3]);
  }
  fence_async_smem();
  bar_sync(3 + wg, 128);
  if (tid == 0) {
    tma_st(&p.out, cg * 128 + wg * 64, tb * 80, sb + XROFF + wg * XCH);
    bulk_commit();
    bulk_wait_read();
    STAMP(27 + 4 * wg);
  }
}

__global__ void __launch_bounds__(384, 1) fused_kernel(const __grid_constant__ Params p) {
  extern __shared__ __align__(1024) unsigned char smem[];
  uint32_t sb = (uint32_t)__cvta_generic_to_shared(smem);
  asm volatile("mov.u32 %0, %0;" : "+r"(sb));
  const int b = blockIdx.x;
  const int warp = __shfl_sync(0xffffffffu, threadIdx.x >> 5, 0), lane = threadIdx.x & 31;
  if (warp >= 8) {
    asm volatile("setmaxnreg.dec.sync.aligned.u32 88;");
    if (warp == 8) producer(p, sb, b, lane);
    else {
      if (elect_one()) {
#pragma unroll
        for (int w = 0; w < 3; w++) {
          if (warp == 9 + w) {
#pragma unroll
            for (int i = I_EMPTY + 13 * w; i < min(I_EMPTY + 13 * w + 13, (int)I_S7); i++)
              mbar_init(sb + MOFF + 8 * i, (i < I_FULL2 || i == I_T1 || i == I_T6) ? 4 : (i >= I_EMPTY2 && i < I_STATS) ? 8 : i == I_STATS ? 32 :
                                           i == I_DUMMY ? 100000 : ((i >= I_STGF && i <= I_MF) || i == I_S1F) ? 128 : 1);
          }
        }
        if (warp == 11) {
          mbar_init(sb + B_S7, b < NMC ? 2 : 1);
          sts64v(sb + W_READY, 0); sts64v(sb + W_B, 0);
          if ((sb & 0x3FFFF) != 1024) TRAP(0);
        }
        fence_async_smem();
      }
      __syncwarp();
      bar_arrive(7, 128);
      bar_sync(0, 384);
      if (warp == 9) agent(p, sb, b, lane);
      else aux(p, sb, b, warp - 10, lane);
    }
  } else {
    if (threadIdx.x < 160) {
      const int i = threadIdx.x;
      sts128(sb + XOFF + (i >> 4) * XCH + TB * 128 + (i & 15) * 16, make_uint4(0x3F803F80u, 0x3F803F80u, 0x3F803F80u, 0x3F803F80u));
      fence_async_smem();
    }
    __syncwarp();
    asm volatile("setmaxnreg.inc.sync.aligned.u32 208;");
    bar_sync(0, 384);
    consumer(p, sb, b, warp >> 2, threadIdx.x & 127);
  }
}

typedef CUresult (*EncodeFn)(CUtensorMap*, CUtensorMapDataType, cuuint32_t, void*, const cuuint64_t*, const cuuint64_t*,
                             const cuuint32_t*, const cuuint32_t*, CUtensorMapInterleave, CUtensorMapSwizzle,
                             CUtensorMapL2promotion, CUtensorMapFloatOOBfill);

void make_map(EncodeFn enc, CUtensorMap* m, const void* ptr, uint64_t rows, uint64_t cols, uint32_t box_rows, uint32_t box_cols = 64) {
  cuuint64_t gd[2] = {cols, rows}, gs[1] = {cols * 2};
  cuuint32_t bd[2] = {box_cols, box_rows}, es[2] = {1, 1};
  CUresult r = enc(m, CU_TENSOR_MAP_DATA_TYPE_BFLOAT16, 2, const_cast<void*>(ptr), gd, gs, bd, es, CU_TENSOR_MAP_INTERLEAVE_NONE,
                   box_cols == 64 ? CU_TENSOR_MAP_SWIZZLE_128B : CU_TENSOR_MAP_SWIZZLE_64B, CU_TENSOR_MAP_L2_PROMOTION_L2_128B, CU_TENSOR_MAP_FLOAT_OOB_FILL_NONE);
  if (r != CUDA_SUCCESS) fprintf(stderr, "cuTensorMapEncodeTiled failed: %d\n", (int)r);
}

void make_map3(EncodeFn enc, CUtensorMap* m, const void* ptr, uint64_t rows) {
  cuuint64_t gd[3] = {64, rows, 10}, gs[2] = {D_ * 2, 128};
  cuuint32_t bd[3] = {64, 64, 2}, es[3] = {1, 1, 1};
  CUresult r = enc(m, CU_TENSOR_MAP_DATA_TYPE_BFLOAT16, 3, const_cast<void*>(ptr), gd, gs, bd, es, CU_TENSOR_MAP_INTERLEAVE_NONE,
                   CU_TENSOR_MAP_SWIZZLE_128B, CU_TENSOR_MAP_L2_PROMOTION_L2_128B, CU_TENSOR_MAP_FLOAT_OOB_FILL_NONE);
  if (r != CUDA_SUCCESS) fprintf(stderr, "cuTensorMapEncodeTiled failed: %d\n", (int)r);
}

}

extern "C" void kernel_launch(void* const* d_in, const int* in_sizes, int n_in, void* d_out, int out_size) {
  (void)in_sizes; (void)n_in; (void)out_size;
  static EncodeFn enc = nullptr;
  static void *pH = nullptr, *pPQ = nullptr, *pM = nullptr, *pKV = nullptr, *pKvp = nullptr, *pZp = nullptr, *pSy = nullptr,
              *pMask = nullptr, *pB = nullptr, *pZ = nullptr;
  if (!enc) {
    void* fn = nullptr;
    cudaDriverEntryPointQueryResult st;
    cudaGetDriverEntryPoint("cuTensorMapEncodeTiled", &fn, cudaEnableDefault, &st);
    enc = (EncodeFn)fn;
    cudaGetSymbolAddress(&pH, g_H); cudaGetSymbolAddress(&pPQ, g_PQ); cudaGetSymbolAddress(&pM, g_M); cudaGetSymbolAddress(&pKV, g_KVT);
    cudaGetSymbolAddress(&pKvp, g_kvp); cudaGetSymbolAddress(&pZp, g_zp); cudaGetSymbolAddress(&pSy, g_sync);
    cudaGetSymbolAddress(&pMask, g_mask); cudaGetSymbolAddress(&pB, g_B); cudaGetSymbolAddress(&pZ, g_z);
    cudaFuncSetAttribute(fused_kernel, cudaFuncAttributeMaxDynamicSharedMemorySize, SMEM_BYTES);
  }
  Params p;
  const void *x = d_in[0], *wqkv = d_in[1], *wo = d_in[2], *w1 = d_in[4], *w3 = d_in[5], *w2 = d_in[6];
  make_map(enc, &p.x1, x, S_, D_, TB);
  make_map(enc, &p.wqkv, wqkv, D_, 3 * D_, 64);
  make_map(enc, &p.w1, w1, D_, F_, 64);
  make_map(enc, &p.w3, w3, D_, F_, 64);
  make_map(enc, &p.hst, pH, S_, F_, TB);
  make_map(enc, &p.pqst, pPQ, S_, D_, TB);
  make_map3(enc, &p.w2, w2, F_);
  make_map3(enc, &p.mm, pM, D_);
  make_map(enc, &p.hld, pH, S_, F_, 80);
  make_map(enc, &p.ald, pPQ, S_, D_, 80);
  make_map(enc, &p.xres, x, S_, D_, 80);
  make_map(enc, &p.out, d_out, S_, D_, 80);
  make_map(enc, &p.kva, pKV, 2 * D_, KTP, 64);
  make_map(enc, &p.kvb, pKV, 2 * D_, KTP, 64, 32);
  make_map(enc, &p.vld, pKV, 2 * D_, KTP, 60);
  make_map(enc, &p.msk, pMask, 4, KTP, 4);
  make_map(enc, &p.bld, pB, 11 * 64, 64, 64);
  make_map(enc, &p.wom, wo, D_, D_, 64);
  make_map(enc, &p.mst, pM, D_, D_, 60);
  p.wo = (const __nv_bfloat16*)wo;
  p.w2p = (const __nv_bfloat16*)w2;
  p.mask_p = (__nv_bfloat16*)pMask; p.b_p = (__nv_bfloat16*)pB; p.z = (float*)pZ; p.pq_p = (__nv_bfloat16*)pPQ;
  p.zero = 0;
  p.kvp = (float*)pKvp; p.zp = (float*)pZp; p.sy = (Sync*)pSy;
  fused_kernel<<<NCTA, 384, SMEM_BYTES>>>(p);
}
```

```cpp
#include <cuda_runtime.h>
#include <cuda_bf16.h>
#include <cuda.h>
#include <stdint.h>
#include <stdio.h>
#include <math.h>

namespace {

constexpr int S_ = 2048, D_ = 640, F_ = 1728;
constexpr int TB = 94;
constexpr int NRB = 22;
constexpr int NCTA = 132;
constexpr int KTP = NRB * 96;
constexpr int NKVC = 121;
constexpr int NMC = 110;
constexpr int NS1 = 5;
constexpr int NS2 = 8;
constexpr uint32_t ST2 = 26624;
constexpr int NK2 = 37;

constexpr uint32_t XOFF = 0;
constexpr uint32_t XCH = 12288;
constexpr uint32_t WOFF = 122880;
constexpr uint32_t SOFF = 204800;
constexpr uint32_t MOFF = 229376;
enum {
  I_FULL = 0, I_XFULL = 5, I_EMPTY = 15, I_FULL2 = 20, I_EMPTY2 = 28, I_STATS = 36, I_XRES, I_STG, I_STGF = I_STG + 2, I_KVF = I_STGF + 2,
  I_MF, I_DUMMY, I_WO, I_AL, I_PD, I_T1, I_S1F, I_S1E, I_FIN, I_S7, I_END
};
constexpr uint32_t B_FULL = MOFF + 8 * I_FULL;
constexpr uint32_t B_XFULL = MOFF + 8 * I_XFULL;
constexpr uint32_t B_EMPTY = MOFF + 8 * I_EMPTY;
constexpr uint32_t B_FULL2 = MOFF + 8 * I_FULL2;
constexpr uint32_t B_EMPTY2 = MOFF + 8 * I_EMPTY2;
constexpr uint32_t B_STATS = MOFF + 8 * I_STATS;
constexpr uint32_t B_XRES = MOFF + 8 * I_XRES;
constexpr uint32_t B_STG = MOFF + 8 * I_STG;
constexpr uint32_t B_STGF = MOFF + 8 * I_STGF;
constexpr uint32_t B_KVF = MOFF + 8 * I_KVF;
constexpr uint32_t B_MF = MOFF + 8 * I_MF;
constexpr uint32_t B_DUMMY = MOFF + 8 * I_DUMMY;
constexpr uint32_t B_WO = MOFF + 8 * I_WO;
constexpr uint32_t B_AL = MOFF + 8 * I_AL;
constexpr uint32_t B_PD = MOFF + 8 * I_PD;
constexpr uint32_t B_T1 = MOFF + 8 * I_T1;
constexpr uint32_t B_S1F = MOFF + 8 * I_S1F;
constexpr uint32_t B_S1E = MOFF + 8 * I_S1E;
constexpr uint32_t B_FIN = MOFF + 8 * I_FIN;
constexpr uint32_t B_S7 = MOFF + 8 * I_S7;
constexpr uint32_t W_READY = MOFF + 448;
constexpr uint32_t W_KV = MOFF + 452;
constexpr uint32_t W_ZERO = MOFF + 460;
constexpr uint32_t STATS = MOFF + 464;
static_assert(8 * I_END <= 448 && I_S7 - I_EMPTY <= 39, "barriers");
constexpr uint32_t ZS = STATS;
constexpr uint32_t SMEM_BYTES = ZS + 2560;
constexpr uint32_t WOOFF = 7 * ST2;
constexpr uint32_t XROFF = 6 * ST2;
static_assert(SMEM_BYTES <= 232448, "smem");

#define KVS_ 3
#define PACE0 400
#define PACE 330
#define PACE2 320
#define T0_DELAY 5200
#define T0_LEAD 400

struct Sync {
  unsigned long long stats[NRB * 96];
  float z[D_];
  unsigned hflag[NRB * 32];
  unsigned tslot[160];
  unsigned c_kv[32], c_q[32], c_p[32], c_z[32], c_m[32], c_done[32];
  unsigned c_a[32];
};

__device__ __align__(1024) __nv_bfloat16 g_H[S_ * F_];
__device__ __align__(1024) __nv_bfloat16 g_PQ[S_ * D_];
__device__ __align__(1024) __nv_bfloat16 g_M[D_ * D_];
__device__ __align__(1024) __nv_bfloat16 g_KVT[2 * D_ * KTP];
__device__ __align__(1024) __nv_bfloat16 g_mask[4 * KTP];
__device__ __align__(1024) float g_kvr[2 * 32 * 400 + 32];
__device__ __align__(1024) float g_kvp[32 * 11 * 400];
__device__ __align__(1024) float g_zp[11 * D_];
__device__ __align__(1024) Sync g_sync;
#define STAMP(i) do {} while (0)

#define TRAP(id) __trap()

struct Params {
  CUtensorMap x1, wqkv, w1, w3, hst, pqst, w2, mm, hld, ald, xres, kva, kvb, vld, msk, wom, mst;
  __nv_bfloat16* outp;
  const __nv_bfloat16* wo;
  const __nv_bfloat16* w2p;
  __nv_bfloat16 *mask_p, *pq_p;
  float *kvp, *zp, *kvr;
  Sync* sy;
  uint32_t zero;
};

__device__ __forceinline__ unsigned long long gtime() { unsigned long long g; asm volatile("mov.u64 %0, %%globaltimer;" : "=l"(g)::"memory"); return g; }
__device__ __forceinline__ uint32_t gtime32() { uint32_t g; asm volatile("mov.u32 %0, %%globaltimer_lo;" : "=r"(g)::"memory"); return g; }
__device__ __forceinline__ uint32_t clk32() { uint32_t c; asm volatile("mov.u32 %0, %%clock;" : "=r"(c)::"memory"); return c; }
__device__ __forceinline__ bool elect_one() { uint32_t p; asm volatile("{.reg .pred P; elect.sync _|P, 0xffffffff; selp.u32 %0,1,0,P;}" : "=r"(p)); return p; }
__device__ __forceinline__ void mbar_init(uint32_t bar, uint32_t cnt) { asm volatile("mbarrier.init.shared::cta.b64 [%0], %1;" ::"r"(bar), "r"(cnt) : "memory"); }
__device__ __forceinline__ void mbar_expect_tx(uint32_t bar, uint32_t bytes) { asm volatile("mbarrier.arrive.expect_tx.shared::cta.b64 _, [%0], %1;" ::"r"(bar), "r"(bytes) : "memory"); }
__device__ __forceinline__ void mbar_arrive(uint32_t bar) { asm volatile("mbarrier.arrive.shared::cta.b64 _, [%0];" ::"r"(bar) : "memory"); }
__device__ __forceinline__ bool mbar_test(uint32_t bar, uint32_t parity) {
  uint32_t ok;
  asm volatile("{.reg .pred p; mbarrier.test_wait.parity.shared::cta.b64 p, [%1], %2; selp.u32 %0,1,0,p;}" : "=r"(ok) : "r"(bar), "r"(parity) : "memory");
  return ok;
}
__device__ __forceinline__ bool mbar_try(uint32_t bar, uint32_t parity) {
  uint32_t ok;
  asm volatile("{.reg .pred p; mbarrier.try_wait.parity.shared::cta.b64 p, [%1], %2; selp.u32 %0,1,0,p;}" : "=r"(ok) : "r"(bar), "r"(parity) : "memory");
  return ok;
}
constexpr uint32_t SPIN_LIMIT = 1u << 22;
__device__ __forceinline__ void mbar_wait(uint32_t bar, uint32_t parity) {
  asm volatile("{\n.reg .pred p;\n.reg .u32 c;\nmov.u32 c, 0;\n"
               "LW:\nmbarrier.try_wait.parity.shared::cta.b64 p, [%0], %1;\n@p bra LD;\n"
               "add.u32 c, c, 1;\nsetp.lt.u32 p, c, %2;\n@p bra LW;\ntrap;\nLD:\n}" ::"r"(bar), "r"(parity), "n"(SPIN_LIMIT) : "memory");
}
__device__ __forceinline__ void mbar_spin(uint32_t bar, uint32_t parity) {
  asm volatile("{\n.reg .pred p;\nLW:\nmbarrier.try_wait.parity.shared::cta.b64 p, [%0], %1;\n@!p bra LW;\n}" ::"r"(bar), "r"(parity) : "memory");
}
__device__ __forceinline__ void tma_ld(uint32_t dst, const CUtensorMap* m, int c0, int c1, uint32_t bar) {
  asm volatile("cp.async.bulk.tensor.2d.shared::cluster.global.mbarrier::complete_tx::bytes [%0], [%1, {%3,%4}], [%2];"
               ::"r"(dst), "l"(m), "r"(bar), "r"(c0), "r"(c1) : "memory");
}
__device__ __forceinline__ void expect_e(uint32_t bar, uint32_t bytes) {
  asm volatile("{.reg .pred P; elect.sync _|P, 0xffffffff; @P mbarrier.arrive.expect_tx.shared::cta.b64 _, [%0], %1;}" ::"r"(bar), "r"(bytes) : "memory");
}
__device__ __forceinline__ void tma_ld_e(uint32_t dst, const CUtensorMap* m, int c0, int c1, uint32_t bar) {
  asm volatile("{.reg .pred P; elect.sync _|P, 0xffffffff;\n"
               "@P cp.async.bulk.tensor.2d.shared::cluster.global.mbarrier::complete_tx::bytes [%0], [%1, {%3,%4}], [%2];}"
               ::"r"(dst), "l"(m), "r"(bar), "r"(c0), "r"(c1) : "memory");
}
__device__ __forceinline__ void tma_ld3_e(uint32_t dst, const CUtensorMap* m, int c1, int c2, uint32_t bar) {
  asm volatile("{.reg .pred P; elect.sync _|P, 0xffffffff;\n"
               "@P cp.async.bulk.tensor.3d.shared::cluster.global.mbarrier::complete_tx::bytes [%0], [%1, {0,%3,%4}], [%2];}"
               ::"r"(dst), "l"(m), "r"(bar), "r"(c1), "r"(c2) : "memory");
}
__device__ __forceinline__ void tma_st(const CUtensorMap* m, int c0, int c1, uint32_t src) {
  asm volatile("cp.async.bulk.tensor.2d.global.shared::cta.bulk_group [%0, {%2,%3}], [%1];" ::"l"(m), "r"(src), "r"(c0), "r"(c1) : "memory");
}
__device__ __forceinline__ void bulk_ld(uint32_t dst, const void* src, uint32_t bytes, uint32_t bar) {
  asm volatile("cp.async.bulk.shared::cluster.global.mbarrier::complete_tx::bytes [%0], [%1], %2, [%3];" ::"r"(dst), "l"(src), "r"(bytes), "r"(bar) : "memory");
}
__device__ __forceinline__ void bulk_st(void* dst, uint32_t src, uint32_t bytes) {
  asm volatile("cp.async.bulk.global.shared::cta.bulk_group [%0], [%1], %2;" ::"l"(dst), "r"(src), "r"(bytes) : "memory");
}
__device__ __forceinline__ void tma_pf(const CUtensorMap* m, int c0, int c1) {
  asm volatile("cp.async.bulk.prefetch.tensor.2d.L2.global.tile [%0, {%1,%2}];" ::"l"(m), "r"(c0), "r"(c1) : "memory");
}
__device__ __forceinline__ void bulk_pf(const void* p, uint32_t bytes) { asm volatile("cp.async.bulk.prefetch.L2.global [%0], %1;" ::"l"(p), "r"(bytes) : "memory"); }
__device__ __forceinline__ void desc_pf(const CUtensorMap* m) { asm volatile("prefetch.tensormap [%0];" ::"l"(m) : "memory"); }
__device__ __forceinline__ void bulk_commit() { asm volatile("cp.async.bulk.commit_group;" ::: "memory"); }
__device__ __forceinline__ void bulk_wait_read() { asm volatile("cp.async.bulk.wait_group.read 0;" ::: "memory"); }
__device__ __forceinline__ void bulk_wait_all() { asm volatile("cp.async.bulk.wait_group 0;" ::: "memory"); }
__device__ __forceinline__ void fence_async_smem() { asm volatile("fence.proxy.async.shared::cta;" ::: "memory"); }
__device__ __forceinline__ void fence_async_global() { asm volatile("fence.proxy.async.global;" ::: "memory"); }
__device__ __forceinline__ void bar_sync(int id, int n) { asm volatile("bar.sync %0, %1;" ::"r"(id), "r"(n) : "memory"); }
__device__ __forceinline__ void bar_arrive(int id, int n) { asm volatile("bar.arrive %0, %1;" ::"r"(id), "r"(n) : "memory"); }
__device__ __forceinline__ void wg_fence() { asm volatile("wgmma.fence.sync.aligned;" ::: "memory"); }
__device__ __forceinline__ void wg_commit() { asm volatile("wgmma.commit_group.sync.aligned;" ::: "memory"); }
template <int N> __device__ __forceinline__ void wg_wait() { asm volatile("wgmma.wait_group.sync.aligned %0;" ::"n"(N) : "memory"); }
template <int N> __device__ __forceinline__ void keep(float (&d)[N]) {
#pragma unroll
  for (int i = 0; i < N; i++) asm volatile("" : "+f"(d[i])::"memory");
}
__device__ __forceinline__ unsigned ld_rlx(const unsigned* p) { unsigned v; asm volatile("ld.relaxed.gpu.global.u32 %0, [%1];" : "=r"(v) : "l"(p) : "memory"); return v; }
__device__ __forceinline__ unsigned long long ld_rlx64(const unsigned long long* p) { unsigned long long v; asm volatile("ld.relaxed.gpu.global.u64 %0, [%1];" : "=l"(v) : "l"(p) : "memory"); return v; }
__device__ __forceinline__ void st_rlx(unsigned* p, unsigned v) { asm volatile("st.relaxed.gpu.global.u32 [%0], %1;" ::"l"(p), "r"(v) : "memory"); }
__device__ __forceinline__ void st_rlx64(unsigned long long* p, unsigned long long v) { asm volatile("st.relaxed.gpu.global.u64 [%0], %1;" ::"l"(p), "l"(v) : "memory"); }
__device__ __forceinline__ void fence_acq() { asm volatile("fence.acquire.gpu;" ::: "memory"); }
__device__ __forceinline__ void red_rlx(unsigned* p, unsigned v) { asm volatile("red.relaxed.gpu.global.add.u32 [%0], %1;" ::"l"(p), "r"(v) : "memory"); }
__device__ __forceinline__ void fence_rel() { asm volatile("fence.release.gpu;" ::: "memory"); }
__device__ __forceinline__ float valid(float a) { return __uint_as_float(__float_as_uint(a) | 1u); }
__device__ __forceinline__ void st_valid2(void* p, float a, float b) {
  asm volatile("st.relaxed.gpu.global.b64 [%0], %1;" ::"l"(p), "l"(((unsigned long long)(__float_as_uint(b) | 1u) << 32) | (__float_as_uint(a) | 1u)) : "memory");
}
__device__ __forceinline__ uint4 ld_rlx128(const void* p) {
  unsigned long long a, b;
  asm volatile("ld.relaxed.gpu.global.v2.b64 {%0,%1}, [%2];" : "=l"(a), "=l"(b) : "l"(p) : "memory");
  return make_uint4((uint32_t)a, (uint32_t)(a >> 32), (uint32_t)b, (uint32_t)(b >> 32));
}
__device__ __forceinline__ void red_rel(unsigned* p, unsigned v) { asm volatile("red.release.gpu.global.add.u32 [%0], %1;" ::"l"(p), "r"(v) : "memory"); }
__device__ __forceinline__ unsigned lds_acq(uint32_t a) { unsigned v; asm volatile("ld.acquire.cta.shared::cta.u32 %0, [%1];" : "=r"(v) : "r"(a) : "memory"); return v; }
__device__ __forceinline__ void sts_rel(uint32_t a, unsigned v) { asm volatile("st.release.cta.shared::cta.u32 [%0], %1;" ::"r"(a), "r"(v) : "memory"); }
__device__ __forceinline__ unsigned long long lds64v(uint32_t a) { unsigned long long v; asm volatile("ld.volatile.shared::cta.u64 %0, [%1];" : "=l"(v) : "r"(a) : "memory"); return v; }
__device__ __forceinline__ void sts64v(uint32_t a, unsigned long long v) { asm volatile("st.volatile.shared::cta.u64 [%0], %1;" ::"r"(a), "l"(v) : "memory"); }
__device__ __forceinline__ uint4 lds128(uint32_t a) { uint4 v; asm volatile("ld.shared.v4.u32 {%0,%1,%2,%3}, [%4];" : "=r"(v.x), "=r"(v.y), "=r"(v.z), "=r"(v.w) : "r"(a) : "memory"); return v; }
__device__ __forceinline__ float4 lds128f(uint32_t a) { float4 v; asm volatile("ld.shared.v4.f32 {%0,%1,%2,%3}, [%4];" : "=f"(v.x), "=f"(v.y), "=f"(v.z), "=f"(v.w) : "r"(a) : "memory"); return v; }
__device__ __forceinline__ void sts128(uint32_t a, uint4 v) { asm volatile("st.shared.v4.u32 [%0], {%1,%2,%3,%4};" ::"r"(a), "r"(v.x), "r"(v.y), "r"(v.z), "r"(v.w) : "memory"); }
__device__ __forceinline__ void stsm4t(uint32_t a, uint32_t r0, uint32_t r1, uint32_t r2, uint32_t r3) {
  asm volatile("stmatrix.sync.aligned.m8n8.x4.trans.shared.b16 [%0], {%1,%2,%3,%4};" ::"r"(a), "r"(r0), "r"(r1), "r"(r2), "r"(r3) : "memory");
}
__device__ __forceinline__ void stsm4(uint32_t a, uint32_t r0, uint32_t r1, uint32_t r2, uint32_t r3) {
  asm volatile("stmatrix.sync.aligned.m8n8.x4.shared.b16 [%0], {%1,%2,%3,%4};" ::"r"(a), "r"(r0), "r"(r1), "r"(r2), "r"(r3) : "memory");
}
__device__ __forceinline__ void ldsm4t(uint32_t a, uint32_t& r0, uint32_t& r1, uint32_t& r2, uint32_t& r3) {
  asm volatile("ldmatrix.sync.aligned.m8n8.x4.trans.shared.b16 {%0,%1,%2,%3}, [%4];" : "=r"(r0), "=r"(r1), "=r"(r2), "=r"(r3) : "r"(a) : "memory");
}
__device__ __forceinline__ uint32_t pack2(float lo, float hi) { uint32_t r; asm("cvt.rn.bf16x2.f32 %0, %1, %2;" : "=r"(r) : "f"(hi), "f"(lo)); return r; }
__device__ __forceinline__ float bf_lo(uint32_t v) { return __uint_as_float(v << 16); }
__device__ __forceinline__ float bf_hi(uint32_t v) { return __uint_as_float(v & 0xffff0000u); }
__device__ __forceinline__ float ex2(float x) { float y; asm("ex2.approx.ftz.f32 %0, %1;" : "=f"(y) : "f"(x)); return y; }
__device__ __forceinline__ float rcp(float x) { float y; asm("rcp.approx.ftz.f32 %0, %1;" : "=f"(y) : "f"(x)); return y; }
constexpr float LOG2E = 1.4426950408889634f, LN2 = 0.6931471805599453f;
__device__ __forceinline__ float silu(float g) { return g * rcp(1.f + ex2(g * -1.4426950408889634f)); }
__device__ __forceinline__ float phi_l(float yl) { return fmaxf(fmaf(yl, LN2, 1.000001f), __saturatef(ex2(yl) + 1e-6f)); }
__host__ __device__ constexpr uint32_t dlo(uint32_t off) { return ((1024u + off) >> 4) | (1u << 16); }
__device__ __forceinline__ void arrive_elect(uint32_t bar) {
  asm volatile("{.reg .pred P; elect.sync _|P, 0xffffffff; @P mbarrier.arrive.shared::cta.b64 _, [%0];}" ::"r"(bar) : "memory");
}
__device__ __forceinline__ void wait_count(const unsigned* p, unsigned target) {
  if ((threadIdx.x & 31) == 0) {
    uint32_t c = 0;
    while (ld_rlx(p) < target) { if (++c > SPIN_LIMIT) TRAP(target); }
    fence_acq();
  }
  __syncwarp();
}

__device__ __forceinline__ void wgmma_n96_first(float (&d)[48], uint32_t da, uint32_t db) {
  asm volatile("{.reg .pred p; .reg .b64 da, db; setp.ne.b32 p, 0, 0;\n"
    "mov.b64 da, {%48, 0x40000040}; mov.b64 db, {%49, 0x40000040};\n"
    "wgmma.mma_async.sync.aligned.m64n96k16.f32.bf16.bf16 "
    "{%0, %1, %2, %3, %4, %5, %6, %7, %8, %9, %10, %11, %12, %13, %14, %15, "
    "%16, %17, %18, %19, %20, %21, %22, %23, %24, %25, %26, %27, %28, %29, %30, %31, "
    "%32, %33, %34, %35, %36, %37, %38, %39, %40, %41, %42, %43, %44, %45, %46, %47}, "
    "da, db, p, 1, 1, 1, 0;}"
    : "=f"(d[0]), "=f"(d[1]), "=f"(d[2]), "=f"(d[3]), "=f"(d[4]), "=f"(d[5]), "=f"(d[6]), "=f"(d[7]),
      "=f"(d[8]), "=f"(d[9]), "=f"(d[10]), "=f"(d[11]), "=f"(d[12]), "=f"(d[13]), "=f"(d[14]), "=f"(d[15]),
      "=f"(d[16]), "=f"(d[17]), "=f"(d[18]), "=f"(d[19]), "=f"(d[20]), "=f"(d[21]), "=f"(d[22]), "=f"(d[23]),
      "=f"(d[24]), "=f"(d[25]), "=f"(d[26]), "=f"(d[27]), "=f"(d[28]), "=f"(d[29]), "=f"(d[30]), "=f"(d[31]),
      "=f"(d[32]), "=f"(d[33]), "=f"(d[34]), "=f"(d[35]), "=f"(d[36]), "=f"(d[37]), "=f"(d[38]), "=f"(d[39]),
      "=f"(d[40]), "=f"(d[41]), "=f"(d[42]), "=f"(d[43]), "=f"(d[44]), "=f"(d[45]), "=f"(d[46]), "=f"(d[47])
    : "r"(da), "r"(db));
}
__device__ __forceinline__ void wgmma_n64_kk_first(float (&d)[32], uint32_t da, uint32_t db) {
  asm volatile("{.reg .pred p; .reg .b64 da, db; setp.ne.b32 p, 0, 0;\n"
    "mov.b64 da, {%32, 0x40000040}; mov.b64 db, {%33, 0x40000040};\n"
    "wgmma.mma_async.sync.aligned.m64n64k16.f32.bf16.bf16 "
    "{%0, %1, %2, %3, %4, %5, %6, %7, %8, %9, %10, %11, %12, %13, %14, %15, "
    "%16, %17, %18, %19, %20, %21, %22, %23, %24, %25, %26, %27, %28, %29, %30, %31}, "
    "da, db, p, 1, 1, 0, 0;}"
    : "=f"(d[0]), "=f"(d[1]), "=f"(d[2]), "=f"(d[3]), "=f"(d[4]), "=f"(d[5]), "=f"(d[6]), "=f"(d[7]),
      "=f"(d[8]), "=f"(d[9]), "=f"(d[10]), "=f"(d[11]), "=f"(d[12]), "=f"(d[13]), "=f"(d[14]), "=f"(d[15]),
      "=f"(d[16]), "=f"(d[17]), "=f"(d[18]), "=f"(d[19]), "=f"(d[20]), "=f"(d[21]), "=f"(d[22]), "=f"(d[23]),
      "=f"(d[24]), "=f"(d[25]), "=f"(d[26]), "=f"(d[27]), "=f"(d[28]), "=f"(d[29]), "=f"(d[30]), "=f"(d[31])
    : "r"(da), "r"(db));
}
__device__ __forceinline__ void wgmma_n96(float (&d)[48], uint32_t da, uint32_t db, int sd) {
  asm volatile("{.reg .pred p; .reg .b64 da, db; setp.ne.b32 p, %50, 0;\n"
    "mov.b64 da, {%48, 0x40000040}; mov.b64 db, {%49, 0x40000040};\n"
    "wgmma.mma_async.sync.aligned.m64n96k16.f32.bf16.bf16 "
    "{%0, %1, %2, %3, %4, %5, %6, %7, %8, %9, %10, %11, %12, %13, %14, %15, "
    "%16, %17, %18, %19, %20, %21, %22, %23, %24, %25, %26, %27, %28, %29, %30, %31, "
    "%32, %33, %34, %35, %36, %37, %38, %39, %40, %41, %42, %43, %44, %45, %46, %47}, "
    "da, db, p, 1, 1, 1, 0;}"
    : "+f"(d[0]), "+f"(d[1]), "+f"(d[2]), "+f"(d[3]), "+f"(d[4]), "+f"(d[5]), "+f"(d[6]), "+f"(d[7]),
      "+f"(d[8]), "+f"(d[9]), "+f"(d[10]), "+f"(d[11]), "+f"(d[12]), "+f"(d[13]), "+f"(d[14]), "+f"(d[15]),
      "+f"(d[16]), "+f"(d[17]), "+f"(d[18]), "+f"(d[19]), "+f"(d[20]), "+f"(d[21]), "+f"(d[22]), "+f"(d[23]),
      "+f"(d[24]), "+f"(d[25]), "+f"(d[26]), "+f"(d[27]), "+f"(d[28]), "+f"(d[29]), "+f"(d[30]), "+f"(d[31]),
      "+f"(d[32]), "+f"(d[33]), "+f"(d[34]), "+f"(d[35]), "+f"(d[36]), "+f"(d[37]), "+f"(d[38]), "+f"(d[39]),
      "+f"(d[40]), "+f"(d[41]), "+f"(d[42]), "+f"(d[43]), "+f"(d[44]), "+f"(d[45]), "+f"(d[46]), "+f"(d[47])
    : "r"(da), "r"(db), "r"(sd));
}
__device__ __forceinline__ void wgmma_n80(float (&d)[40], uint32_t da, uint32_t db, int sd) {
  asm volatile("{.reg .pred p; .reg .b64 da, db; setp.ne.b32 p, %42, 0;\n"
    "mov.b64 da, {%40, 0x40000040}; mov.b64 db, {%41, 0x40000040};\n"
    "wgmma.mma_async.sync.aligned.m64n80k16.f32.bf16.bf16 "
    "{%0, %1, %2, %3, %4, %5, %6, %7, %8, %9, %10, %11, %12, %13, %14, %15, "
    "%16, %17, %18, %19, %20, %21, %22, %23, %24, %25, %26, %27, %28, %29, %30, %31, "
    "%32, %33, %34, %35, %36, %37, %38, %39}, "
    "da, db, p, 1, 1, 1, 0;}"
    : "+f"(d[0]), "+f"(d[1]), "+f"(d[2]), "+f"(d[3]), "+f"(d[4]), "+f"(d[5]), "+f"(d[6]), "+f"(d[7]),
      "+f"(d[8]), "+f"(d[9]), "+f"(d[10]), "+f"(d[11]), "+f"(d[12]), "+f"(d[13]), "+f"(d[14]), "+f"(d[15]),
      "+f"(d[16]), "+f"(d[17]), "+f"(d[18]), "+f"(d[19]), "+f"(d[20]), "+f"(d[21]), "+f"(d[22]), "+f"(d[23]),
      "+f"(d[24]), "+f"(d[25]), "+f"(d[26]), "+f"(d[27]), "+f"(d[28]), "+f"(d[29]), "+f"(d[30]), "+f"(d[31]),
      "+f"(d[32]), "+f"(d[33]), "+f"(d[34]), "+f"(d[35]), "+f"(d[36]), "+f"(d[37]), "+f"(d[38]), "+f"(d[39])
    : "r"(da), "r"(db), "r"(sd));
}
__device__ __forceinline__ void wgmma_n64_kk(float (&d)[32], uint32_t da, uint32_t db, int sd) {
  asm volatile("{.reg .pred p; .reg .b64 da, db; setp.ne.b32 p, %34, 0;\n"
    "mov.b64 da, {%32, 0x40000040}; mov.b64 db, {%33, 0x40000040};\n"
    "wgmma.mma_async.sync.aligned.m64n64k16.f32.bf16.bf16 "
    "{%0, %1, %2, %3, %4, %5, %6, %7, %8, %9, %10, %11, %12, %13, %14, %15, "
    "%16, %17, %18, %19, %20, %21, %22, %23, %24, %25, %26, %27, %28, %29, %30, %31}, "
    "da, db, p, 1, 1, 0, 0;}"
    : "+f"(d[0]), "+f"(d[1]), "+f"(d[2]), "+f"(d[3]), "+f"(d[4]), "+f"(d[5]), "+f"(d[6]), "+f"(d[7]),
      "+f"(d[8]), "+f"(d[9]), "+f"(d[10]), "+f"(d[11]), "+f"(d[12]), "+f"(d[13]), "+f"(d[14]), "+f"(d[15]),
      "+f"(d[16]), "+f"(d[17]), "+f"(d[18]), "+f"(d[19]), "+f"(d[20]), "+f"(d[21]), "+f"(d[22]), "+f"(d[23]),
      "+f"(d[24]), "+f"(d[25]), "+f"(d[26]), "+f"(d[27]), "+f"(d[28]), "+f"(d[29]), "+f"(d[30]), "+f"(d[31])
    : "r"(da), "r"(db), "r"(sd));
}
__device__ __forceinline__ void wgmma_n64(float (&d)[32], uint32_t da, uint32_t db, int sd) {
  asm volatile("{.reg .pred p; .reg .b64 da, db; setp.ne.b32 p, %34, 0;\n"
    "mov.b64 da, {%32, 0x40000040}; mov.b64 db, {%33, 0x40000040};\n"
    "wgmma.mma_async.sync.aligned.m64n64k16.f32.bf16.bf16 "
    "{%0, %1, %2, %3, %4, %5, %6, %7, %8, %9, %10, %11, %12, %13, %14, %15, "
    "%16, %17, %18, %19, %20, %21, %22, %23, %24, %25, %26, %27, %28, %29, %30, %31}, "
    "da, db, p, 1, 1, 1, 0;}"
    : "+f"(d[0]), "+f"(d[1]), "+f"(d[2]), "+f"(d[3]), "+f"(d[4]), "+f"(d[5]), "+f"(d[6]), "+f"(d[7]),
      "+f"(d[8]), "+f"(d[9]), "+f"(d[10]), "+f"(d[11]), "+f"(d[12]), "+f"(d[13]), "+f"(d[14]), "+f"(d[15]),
      "+f"(d[16]), "+f"(d[17]), "+f"(d[18]), "+f"(d[19]), "+f"(d[20]), "+f"(d[21]), "+f"(d[22]), "+f"(d[23]),
      "+f"(d[24]), "+f"(d[25]), "+f"(d[26]), "+f"(d[27]), "+f"(d[28]), "+f"(d[29]), "+f"(d[30]), "+f"(d[31])
    : "r"(da), "r"(db), "r"(sd));
}

__device__ __forceinline__ void role1(int b, int& G, int& rb) {
  const int hi = b >= 66, c = b - 66 * hi;
  rb = c / 3; G = 3 * hi + (c - 3 * rb);
}
__device__ __forceinline__ void role2(int b, int& tb, int& cg) {
  tb = b / 5; cg = b - 5 * tb;
}
enum { T_KV = 0, T_QQ = 1, T_FFN = 2 };
__device__ __forceinline__ int step_info(int G, int s, int& i) {
  if (s < 2 && G < 5) { i = 2 * G + s; return T_KV; }
  if (s == 2 && G > 0) { i = 2 * (G - 1); return T_QQ; }
  i = s < 3 ? s : 3 + 6 * (s - 3) + G;
  return T_FFN;
}
__device__ __forceinline__ void step_src(const Params& p, int G, int s, const CUtensorMap*& m0, const CUtensorMap*& m1, int& c0, int& c1) {
  int i;
  const int ty = step_info(G, s, i);
  m0 = ty == T_FFN ? &p.w1 : &p.wqkv; m1 = ty == T_FFN ? &p.w3 : &p.wqkv;
  c0 = 64 * i + (ty == T_KV ? 640 : 0); c1 = c0 + (ty == T_KV ? 640 : (ty == T_QQ ? 64 : 0));
}

__host__ __device__ constexpr uint32_t p2_off(int slot) { return slot * ST2; }

__device__ __forceinline__ void wait_ready(uint32_t sb, uint32_t n) {
  uint32_t c = 0;
  while (lds_acq(sb + W_READY) < n) { if (++c > (SPIN_LIMIT << 4)) TRAP(0); }
}
__device__ __forceinline__ void p2_load(const CUtensorMap& mA, const CUtensorMap& mB, uint32_t dA, uint32_t fb, uint32_t wb, uint32_t wp,
                                        int ca, int rowb, int k0, uint32_t& cnext, uint32_t pace, int b, int i) {
  mbar_spin(wb, wp);
  expect_e(fb, ST2);
  while ((int)(clk32() - cnext) < 0) {}
  cnext += pace;
  tma_ld_e(dA + 16384, &mB, k0, rowb, fb);
  tma_ld3_e(dA, &mA, k0, ca, fb);
}

struct Watch {
  const unsigned *f0, *f1;
  unsigned t0v, t1v, published;
  __device__ __forceinline__ Watch(Sync* sy, int b, int lane) {
    int tb, cg;
    role2(min(b, 129), tb, cg);
    t0v = 1; t1v = 1; published = b < 130 ? 0 : NK2;
    if (lane < 27) { f0 = &sy->hflag[(tb * 80) / TB * 32 + lane]; f1 = &sy->hflag[min(tb * 80 + 79, S_ - 1) / TB * 32 + lane]; }
    else { f0 = &sy->c_m[0]; f1 = &sy->c_a[tb]; t0v = NMC; t1v = (tb == 25) ? 3 : 5; }
  }
  __device__ __forceinline__ void check(unsigned v0, unsigned v1, uint32_t sb, int lane) {
    const unsigned m = __ballot_sync(0xffffffffu, (v0 >= t0v) & (v1 >= t1v));
    unsigned n = __ffs(~m | 0x10000000u) - 1;
    if (n == 28) n = NK2;
    if (n > published) {
      published = n;
      fence_acq();
      __syncwarp();
      if (lane == 0) {
        asm volatile("red.release.cta.shared::cta.max.u32 [%0], %1;" ::"r"(sb + W_READY), "r"(n) : "memory");
      }
    }
  }
};

__device__ __forceinline__ void producer(const Params& p, uint32_t sb, int b, int lane) {
  int G, rb;
  role1(b, G, rb);
  const uint32_t gt0 = gtime32(), ck0 = clk32();
  uint32_t tmine = 0, ts[5];
  {
    const CUtensorMap *m0, *m1; int c0, c1;
    step_src(p, G, 0, m0, m1, c0, c1);
    if (elect_one()) {
      STAMP(48);
      mbar_init(sb + B_FULL, 1); mbar_init(sb + B_XFULL, 1);
      fence_async_smem();
    }
    __syncwarp();
#pragma unroll 1
    for (int kt = 0; kt < 10; kt++) {
      if (kt == 1) {
        if (elect_one()) {
#pragma unroll
          for (int i = 1; i < I_EMPTY; i++) if (i != I_XFULL) mbar_init(sb + MOFF + 8 * i, 1);
          fence_async_smem();
        }
        __syncwarp();
        bar_arrive(0, 384);
      }
      if (kt < NS1) {
        expect_e(sb + B_FULL + 8 * kt, 16384);
        tma_ld_e(sb + WOFF + kt * 16384, m0, c0, kt * 64, sb + B_FULL + 8 * kt);
        tma_ld_e(sb + WOFF + kt * 16384 + 8192, m1, c1, kt * 64, sb + B_FULL + 8 * kt);
      }
      expect_e(sb + B_XFULL + 8 * kt, TB * 128);
      tma_ld_e(sb + XOFF + kt * XCH, &p.x1, kt * 64, rb * TB, sb + B_XFULL + 8 * kt);
    }
    if (elect_one()) STAMP(49);
    bar_sync(7, 128);
  }
#pragma unroll 1
  for (int s = 0; s < 7; s++) {
    const CUtensorMap *m0, *m1; int c0, c1;
    step_src(p, G, s, m0, m1, c0, c1);
    if (s == KVS_ + 1) {
      uint32_t c = 0;
      while (lds_acq(sb + W_KV) == 0) { if (++c > (SPIN_LIMIT << 4)) TRAP(0); }
      const int kcol = (b % 11) * 192, krow = min(b / 11, 10) * 60;
#pragma unroll 1
      for (int j = 0; j < 3; j++) {
        mbar_spin(sb + B_EMPTY + 8 * j, 1);
        expect_e(sb + B_FULL + 8 * j, 16384);
        tma_ld_e(sb + WOFF + j * 16384, &p.kva, kcol + 64 * j, krow, sb + B_FULL + 8 * j);
        tma_ld_e(sb + WOFF + j * 16384 + 8192, &p.vld, kcol + 64 * j, D_ + krow, sb + B_FULL + 8 * j);
        tma_ld_e(sb + WOFF + j * 16384 + 8192 + 60 * 128, &p.msk, kcol + 64 * j, 0, sb + B_FULL + 8 * j);
      }
    }
    if (s == 6) {
      const uint32_t g = __shfl_sync(0xffffffffu, gtime32(), 0);
      const float ns_per_clk = __fdividef((float)(g - gt0), (float)(clk32() - ck0));
      tmine = (g + (uint32_t)(T0_DELAY * ns_per_clk)) | 1u;
      tmine = __shfl_sync(0xffffffffu, tmine, 0);
      if (lane == 0) st_rlx(&p.sy->tslot[b], tmine);
    }
    const uint32_t rot = s > KVS_;
    const uint32_t dA = sb + WOFF + rot * (3 * 16384), dB = sb + WOFF - rot * (2 * 16384);
    const uint32_t fA = sb + B_FULL + rot * 24, fB = sb + B_FULL - rot * 16;
#pragma unroll 1
    for (uint32_t h = (s == 0); h < 2; h++) {
      const int k0 = h * 320;
      if (s == 6 && h == 1) {
#pragma unroll
        for (int q = 0; q < 5; q++) ts[q] = (q * 32 + lane < NCTA) ? ld_rlx(&p.sy->tslot[q * 32 + lane]) : tmine;
      }
#pragma unroll
      for (int j = 0; j < 5; j++) {
        const uint32_t fb = (j < 2 ? fA : fB) + 8 * j, dst = (j < 2 ? dA : dB) + j * 16384;
        mbar_spin(fb + (B_EMPTY - B_FULL), (j < 2 ? h : h ^ rot) ^ 1);
        expect_e(fb, 16384);
        tma_ld_e(dst, m0, c0, k0 + j * 64, fb);
        tma_ld_e(dst + 8192, m1, c1, k0 + j * 64, fb);
      }
    }
  }
  if (elect_one()) STAMP(40);
  if (b >= 130) { arrive_elect(sb + B_FIN); return; }
  int tb, cg;
  role2(b, tb, cg);
  const int rowb = tb * 80;
  uint32_t cnext;
  {
    uint32_t c = 0;
    if (b < NMC) {
      mbar_spin(sb + B_EMPTY + 8 * 4, 1);
      expect_e(sb + B_WO, 8192);
      tma_ld_e(sb + WOOFF, &p.wom, (b % 10) * 64, (b / 10) * 60, sb + B_WO);
    }
    while (__any_sync(0xffffffffu, (ts[0] == 0) | (ts[1] == 0) | (ts[2] == 0) | (ts[3] == 0) | (ts[4] == 0))) {
#pragma unroll
      for (int q = 0; q < 5; q++) ts[q] = (q * 32 + lane < NCTA) ? ld_rlx(&p.sy->tslot[q * 32 + lane]) : tmine;
      if (++c > SPIN_LIMIT) TRAP(0);
    }
    int d = 0;
#pragma unroll
    for (int q = 0; q < 5; q++) d = max(d, (int)(ts[q] - tmine));
    const uint32_t T0 = tmine + __reduce_max_sync(0xffffffffu, d);
    Watch w(p.sy, b, lane);
    while (w.published < 15) {
      w.check(ld_rlx(w.f0), ld_rlx(w.f1), sb, lane);
      if (++c > SPIN_LIMIT) TRAP(0);
    }
    arrive_elect(sb + B_PD);
    while ((int)(gtime32() - T0) < 0) { if (++c > (SPIN_LIMIT << 4)) TRAP(0); }
    cnext = clk32() + T0_LEAD;
    if (elect_one()) STAMP(41);
  }
  uint32_t dA = sb, fb = sb + B_FULL2, par = 0;
  int k0 = 0;
#pragma unroll 1
  for (int i = 0; i < 7; i++) {
    p2_load(p.w2, p.hld, dA, fb, sb + (i < 2 ? B_DUMMY : B_T1), i < 2, 2 * cg, rowb, k0, cnext, PACE0, b, i);
    k0 += 64; dA += ST2; fb += 8;
  }
  dA = sb; fb = sb + B_FULL2;
#pragma unroll 1
  for (int kend = 14 * 64; kend <= 27 * 64; kend = (kend == 14 * 64 ? 15 * 64 : kend + 6 * 64)) {
#pragma unroll 1
    do {
      const uint32_t last = dA == sb + 7 * ST2;
      p2_load(p.w2, p.hld, dA, fb, fb + (B_EMPTY2 - B_FULL2), par ^ last, 2 * cg, rowb, k0, cnext, PACE, b, k0 >> 6);
      k0 += 64; dA += ST2; fb += 8;
      if (last) { dA = sb; fb = sb + B_FULL2; par ^= 1; }
    } while (k0 != kend);
    if (kend == 14 * 64) mbar_spin(sb + B_S7, 0);
    else wait_ready(sb, kend == 27 * 64 ? NK2 : (kend >> 6) + 6);
  }
#pragma unroll 1
  for (k0 = 0; k0 < D_; k0 += 64) {
    const uint32_t last = dA == sb + 7 * ST2;
    p2_load(p.mm, p.ald, dA, fb, fb + (B_EMPTY2 - B_FULL2), par ^ last, 2 * cg, rowb, k0, cnext, PACE2, b, 27 + (k0 >> 6));
    dA += ST2; fb += 8;
    if (last) { dA = sb; fb = sb + B_FULL2; par ^= 1; }
  }
  mbar_spin(sb + B_EMPTY2 + 8 * 6, 1);
  expect_e(sb + B_XRES, 2 * 80 * 128);
  tma_ld_e(sb + XROFF, &p.xres, cg * 128, rowb, sb + B_XRES);
  tma_ld_e(sb + XROFF + XCH, &p.xres, cg * 128 + 64, rowb, sb + B_XRES);
  arrive_elect(sb + B_FIN);
  if (elect_one()) STAMP(42);
}

__device__ __forceinline__ void agent(const Params& p, uint32_t sb, int b, int lane) {
  Sync* sy = p.sy;
  int G, rb;
  role1(b, G, rb);
  const CUtensorMap *n0, *n1; int d0, d1;
  step_src(p, G, min(lane + 1, 6), n0, n1, d0, d1);
  if (rb >= 10) { n0 = n1; d0 = d1; }
  d1 = (rb < 10 ? rb : rb - 10) * 64;
  if (lane < 17) desc_pf(&p.x1 + lane);
  mbar_wait(sb + B_XFULL + 8 * 6, 0);
  if (rb < 20 && lane == 0) tma_pf(n0, d0, d1);
  mbar_wait(sb + B_XFULL + 8 * 9, 0);
  if (rb < 20 && lane == 1) tma_pf(n0, d0, d1);
  const int ca = rb * 96 + (rb & 1) * 32, cb = rb * 96 + 64 - (rb & 1) * 64;
  int n1s = 0;
  uint32_t pend = 0;
#pragma unroll 1
  for (int s = 0; s < 7; s++) {
    int ix;
    const int ty = step_info(G, s, ix);
    if (ty != T_FFN) {
      mbar_wait(sb + B_S1F, n1s & 1);
      n1s++;
      if (lane == 0) {
        if (ty == T_QQ) tma_st(&p.pqst, 64 * ix + 64, rb * TB, sb + SOFF + XCH);
        else { tma_st(&p.kva, ca, D_ + 64 * ix, sb + SOFF + XCH); tma_st(&p.kvb, cb, D_ + 64 * ix, sb + SOFF + XCH + 8192); }
        bulk_commit();
        bulk_wait_all();
        mbar_arrive(sb + B_S1E);
      }
      __syncwarp();
    }
    const bool with_m = s == 6 && b < NMC;
    if (with_m) {
      mbar_wait(sb + B_MF, 0);
      if (lane == 0) tma_st(&p.mst, (b % 10) * 64, (b / 10) * 60, sb + WOOFF + 8192);
      __syncwarp();
    }
    mbar_wait(sb + B_STGF + 8 * (s & 1), (s >> 1) & 1);
    if (lane == 0) {
      if (ty == T_FFN) tma_st(&p.hst, 64 * ix, rb * TB, sb + SOFF);
      else if (ty == T_QQ) tma_st(&p.pqst, 64 * ix, rb * TB, sb + SOFF);
      else { tma_st(&p.kva, ca, 64 * ix, sb + SOFF); tma_st(&p.kvb, cb, 64 * ix, sb + SOFF + 8192); }
      bulk_commit();
      bulk_wait_all();
      mbar_arrive(sb + (s == 6 ? B_S7 : B_STG + 8 * (s & 1)));
      if (ty == T_FFN) pend |= 1u << ix;
      if (s >= 4 || ty == T_QQ || (ty == T_KV && s == 1)) {
        fence_rel();
        if (ty != T_FFN) red_rlx(ty == T_QQ ? &sy->c_q[0] : &sy->c_kv[0], 1);
        else
          for (; pend; pend &= pend - 1) red_rlx(&sy->hflag[rb * 32 + __ffs(pend) - 1], 1);
        if (with_m) red_rlx(&sy->c_m[0], 1);
      }
      STAMP(50 + s);
      if (s == 0 && b < 128) {
        bulk_pf(reinterpret_cast<const char*>(p.wo) + b * 6400, 6400);
        bulk_pf(reinterpret_cast<const char*>(p.w2p) + b * 17280, 17280);
      }
    }
    if (rb < 20 && lane == s + 2 && s < 4) tma_pf(n0, d0, d1);
    __syncwarp();
  }
  if (b < 130) mbar_wait(sb + B_PD, 0);
  bar_sync(6, 96);
  unsigned last = 0;
  if (lane == 0) { __threadfence(); last = atomicAdd(&sy->c_done[0], 1) == NCTA - 1; }
  if (__shfl_sync(0xffffffffu, last, 0)) {
    __threadfence();
    uint4* w = reinterpret_cast<uint4*>(sy);
#pragma unroll 1
    for (int i = lane; i < (int)(sizeof(Sync) / 16); i += 32) w[i] = make_uint4(0, 0, 0, 0);
    if (lane == 0) reinterpret_cast<unsigned*>(p.kvr)[2 * 12800] ^= 1u;
  }
  mbar_wait(sb + B_FIN, 0);
}

__device__ __forceinline__ void aux(const Params& p, uint32_t sb, int b, int aw, int lane) {
  Sync* sy = p.sy;
  char* rows = reinterpret_cast<char*>(p.pq_p + (size_t)16 * b * D_);
  const uint32_t abuf = sb + SOFF + XCH;
  if (b == 0) {
#pragma unroll 1
    for (int i = aw * 32 + lane; i < KTP / 8; i += 64) {
      const int rb = i / 12, q = i - 12 * rb;
      const int left = min(TB, S_ - rb * TB) - 8 * ((rb & 1) ? (q < 4 ? q + 8 : q - 4) : q);
      reinterpret_cast<uint4*>(p.mask_p)[i] =
          make_uint4(left > 0 ? 0x3F803F80u : 0u, left > 2 ? 0x3F803F80u : 0u, left > 4 ? 0x3F803F80u : 0u, left > 6 ? 0x3F803F80u : 0u);
    }
    __syncwarp();
    if (lane == 0) red_rel(&sy->c_kv[0], 1);
  }
  if (aw == 0) {
    int G, rb;
    role1(b, G, rb);
    const unsigned long long* src = &sy->stats[rb * 96 + lane];
    unsigned long long v0, v1, v2;
    uint32_t c = 0;
    do {
      v0 = ld_rlx64(src); v1 = ld_rlx64(src + 32); v2 = ld_rlx64(src + 64);
      if (++c > SPIN_LIMIT) TRAP(0);
    } while (v0 == 0 || v1 == 0 || v2 == 0);
    sts64v(sb + STATS + 8 * lane, v0); sts64v(sb + STATS + 256 + 8 * lane, v1); sts64v(sb + STATS + 512 + 8 * lane, v2);
    mbar_arrive(sb + B_STATS);
    __syncwarp();
    wait_count(&sy->c_kv[0], 5 * NRB + 2);
    if (lane == 0) { fence_async_global(); sts_rel(sb + W_KV, 1); STAMP(44); }
    if (b < NKVC) {
      mbar_wait(sb + B_KVF, 0);
      if (lane == 0) {
        STAMP(21);
        const int hg = b / 11, part = b - 11 * hg, nh = hg == 10 ? 2 : 3;
#pragma unroll 1
        for (int hl = 0; hl < nh; hl++) bulk_st(p.kvp + ((3 * hg + hl) * 11 + part) * 400, abuf + 1600 * hl, 1600);
        bulk_st(p.zp + part * D_ + 60 * hg, abuf + 4800, 80 * nh);
        bulk_commit();
        bulk_wait_all();
        red_rlx(&sy->c_p[0], 1);
        STAMP(22);
      }
      __syncwarp();
    }
    if (b < 128) {
      wait_count(&sy->c_q[0], 5 * NRB);
      if (lane == 0) { mbar_expect_tx(sb + B_AL, 10240); bulk_ld(abuf, rows, 10240, sb + B_AL); }
      const uint32_t par = ld_rlx(reinterpret_cast<const unsigned*>(p.kvr) + 2 * 12800);
      const int u = 25 * b + lane, head = u / 100, zu = 2 * b + lane - 25;
      const bool isz = lane >= 25, act = lane < 25 || (lane < 27 && zu < D_ / 4);
      float4* src = isz ? reinterpret_cast<float4*>(p.zp) + zu : reinterpret_cast<float4*>(p.kvp + head * 10 * 400) + u;
      float* dst = isz ? sy->z + 4 * zu : p.kvr + par * 12800 + 4 * u;
      asm volatile("" : "+l"(src), "+l"(dst));
      if (lane == 0) STAMP(23);
      wait_count(&sy->c_p[0], NKVC);
      if (lane == 0) STAMP(36);
      if (act) {
        const int stride = isz ? D_ / 4 : 100;
        uint4 v[11];
        uint32_t all;
        c = 0;
        do {
#pragma unroll
          for (int q = 0; q < 11; q++) v[q] = ld_rlx128(src + q * stride);
          all = 1;
#pragma unroll
          for (int q = 0; q < 11; q++) all &= v[q].x & v[q].y & v[q].z & v[q].w;
          if (++c > SPIN_LIMIT) TRAP(0);
        } while (!all);
        float4 s = make_float4(0.f, 0.f, 0.f, 0.f);
#pragma unroll
        for (int q = 0; q < 11; q++) {
          s.x += __uint_as_float(v[q].x); s.y += __uint_as_float(v[q].y); s.z += __uint_as_float(v[q].z); s.w += __uint_as_float(v[q].w);
        }
        st_valid2(dst, s.x, s.y); st_valid2(dst + 2, s.z, s.w);
        if (isz) red_rlx(&sy->c_z[0], 1);
        else *reinterpret_cast<float4*>(p.kvr + (par ^ 1) * 12800 + 4 * u) = make_float4(0.f, 0.f, 0.f, 0.f);
      }
      __syncwarp();
      if (lane == 0) STAMP(43);
      if (act) {
#pragma unroll 1
        for (int q = 0; q < 11; q++) src[q * (isz ? D_ / 4 : 100)] = make_float4(0.f, 0.f, 0.f, 0.f);
      }
      __syncwarp();
    }
  } else if (b < 128) {
    wait_count(&sy->c_z[0], D_ / 4);
    if (lane == 0) STAMP(39);
    uint4 v[5];
    bool all;
    uint32_t c = 0;
    do {
      all = true;
#pragma unroll
      for (int i = 0; i < 5; i++) v[i] = ld_rlx128(sy->z + 4 * lane + 128 * i);
#pragma unroll
      for (int i = 0; i < 5; i++) all = all && (v[i].x & v[i].y & v[i].z & v[i].w & 1u);
      if (++c > SPIN_LIMIT) TRAP(0);
    } while (!all);
#pragma unroll
    for (int i = 0; i < 5; i++) sts128(sb + ZS + 16 * lane + 512 * i, v[i]);
    if (lane == 0) STAMP(46);
  }
  if (b < 128) {
    bar_sync(5, 64);
    float z[20];
#pragma unroll
    for (int i = 0; i < 5; i++) {
      const float4 t = lds128f(sb + ZS + 80 * lane + 16 * i);
      z[4 * i] = t.x; z[4 * i + 1] = t.y; z[4 * i + 2] = t.z; z[4 * i + 3] = t.w;
    }
#pragma unroll 1
    for (int r = 0; r < 2; r++) {
      mbar_wait(sb + B_AL, r);
      if (aw == 0 && lane == 0) STAMP(59 + r);
#pragma unroll 1
      for (int t0 = 0; t0 < 4; t0 += 2) {
        const uint32_t a = abuf + (4 * aw + t0) * 1280 + 40 * lane;
        uint2 v[2][5];
#pragma unroll
        for (int tk = 0; tk < 2; tk++)
#pragma unroll
          for (int i = 0; i < 5; i++) asm volatile("ld.shared.v2.u32 {%0,%1}, [%2];" : "=r"(v[tk][i].x), "=r"(v[tk][i].y) : "r"(a + tk * 1280 + 8 * i) : "memory");
        float inv[2];
#pragma unroll
        for (int tk = 0; tk < 2; tk++) {
          float den = 1e-6f, den2 = 0.f;
#pragma unroll
          for (int i = 0; i < 5; i++) {
            den = fmaf(bf_lo(v[tk][i].x), z[4 * i], den); den2 = fmaf(bf_hi(v[tk][i].x), z[4 * i + 1], den2);
            den = fmaf(bf_lo(v[tk][i].y), z[4 * i + 2], den); den2 = fmaf(bf_hi(v[tk][i].y), z[4 * i + 3], den2);
          }
          inv[tk] = rcp(den + den2);
        }
#pragma unroll
        for (int tk = 0; tk < 2; tk++)
#pragma unroll
          for (int i = 0; i < 5; i++)
            asm volatile("st.shared.v2.u32 [%0], {%1,%2};" ::"r"(a + tk * 1280 + 8 * i),
                         "r"(pack2(bf_lo(v[tk][i].x) * inv[tk], bf_hi(v[tk][i].x) * inv[tk])),
                         "r"(pack2(bf_lo(v[tk][i].y) * inv[tk], bf_hi(v[tk][i].y) * inv[tk])) : "memory");
      }
      fence_async_smem();
      bar_sync(5, 64);
      if (aw == 0 && lane == 0) {
        bulk_st(rows + r * 10240, abuf, 10240);
        bulk_commit();
        bulk_wait_all();
        if (r == 0) { mbar_expect_tx(sb + B_AL, 10240); bulk_ld(abuf, rows + 10240, 10240, sb + B_AL); }
        else { STAMP(63); red_rel(&sy->c_a[b / 5], 1); STAMP(47); }
      }
      __syncwarp();
    }
  }
  if (aw == 1) {
    mbar_wait(sb + B_T1, 0);
    Watch w(sy, b, lane);
    uint32_t c = 0;
#pragma unroll 1
    while (w.published < NK2) {
      w.check(ld_rlx(w.f0), ld_rlx(w.f1), sb, lane);
      if (++c > SPIN_LIMIT) TRAP(0);
    }
  }
  bar_arrive(6, 96);
}

__device__ __forceinline__ void ln_stats(uint32_t sb, int tid, int G, int rb, Sync* sy) {
  const int tok = 16 * G + (tid >> 3);
  uint32_t a = sb + XOFF + tok * 128;
  mbar_spin(sb + B_XFULL, 0);
  uint32_t p0;
  asm volatile("ld.shared.u32 %0, [%1];" : "=r"(p0) : "r"(a) : "memory");
  const float piv = bf_lo(p0);
  float s4[4] = {0.f, 0.f, 0.f, 0.f}, q4[4] = {0.f, 0.f, 0.f, 0.f};
  a += (tid & 7) * 16;
#pragma unroll 1
  for (int c = 0; c < 10; c += 2) {
    mbar_spin(sb + B_XFULL + 8 * c + 8, 0);
    mbar_spin(sb + B_XFULL + 8 * c, 0);
    const uint4 v = lds128(a + c * XCH), u = lds128(a + c * XCH + XCH);
    const uint32_t w[8] = {v.x, v.y, v.z, v.w, u.x, u.y, u.z, u.w};
#pragma unroll
    for (int q = 0; q < 8; q++) {
      const float d0 = bf_lo(w[q]) - piv, d1 = bf_hi(w[q]) - piv;
      s4[q & 3] += d0 + d1;
      q4[q & 3] = fmaf(d0, d0, fmaf(d1, d1, q4[q & 3]));
    }
  }
  float sm = (s4[0] + s4[1]) + (s4[2] + s4[3]), sq = (q4[0] + q4[1]) + (q4[2] + q4[3]);
#pragma unroll
  for (int o = 1; o < 8; o <<= 1) { sm += __shfl_xor_sync(0xffffffffu, sm, o); sq += __shfl_xor_sync(0xffffffffu, sq, o); }
  if ((tid & 7) == 0) {
    const float dm = sm * (1.f / D_);
    const float var = fmaxf(sq * (1.f / D_) - dm * dm, 0.f);
    uint32_t rl = __float_as_uint(rsqrtf(var + 1e-5f) * LOG2E);
    if (tok >= min(TB, S_ - rb * TB) || rl == 0) rl = 0x80000000u;
    st_rlx64(&sy->stats[rb * 96 + tok], ((unsigned long long)rl << 32) | __float_as_uint(-(piv + dm)));
  }
}

__device__ __forceinline__ void load_stats(float (&st)[48], uint32_t sb, int lane) {
  mbar_spin(sb + B_STATS, 0);
#pragma unroll
  for (int j = 0; j < 12; j++) {
    const float4 v = lds128f(sb + STATS + 16 * (lane & 3) + 64 * j);
    st[4 * j] = v.x; st[4 * j + 1] = v.y; st[4 * j + 2] = v.z; st[4 * j + 3] = v.w;
  }
}
__device__ __forceinline__ void chain(float& v, uint32_t after, uint32_t zero) {
  v = __uint_as_float(__float_as_uint(v) | (after & zero));
}
__device__ __forceinline__ uint32_t token(uint32_t a) { uint32_t v; asm volatile("ld.volatile.shared::cta.u32 %0, [%1];" : "=r"(v) : "r"(a) : "memory"); return v; }
__device__ __forceinline__ void link(float& v, uint32_t tok) { v = __uint_as_float(__float_as_uint(v) | tok); }
template <bool PHI, bool TRANS>
__device__ __forceinline__ void epi_attn(const float (&a)[48], const float (&st)[48], int lane, uint32_t zero, uint32_t zaddr,
                                         uint32_t dst, uint32_t dst2) {
  float c0 = __shfl_sync(0xffffffffu, a[44], lane | 3), c1 = __shfl_sync(0xffffffffu, a[46], lane | 3);
  uint32_t plo = 0, phi_ = 0, tok = 0;
#pragma unroll
  for (int j = 0; j < 12; j++) {
    float y[4];
#pragma unroll
    for (int q = 0; q < 4; q++) {
      const float yl = fmaf(st[4 * j + 2 * (q & 1)], q < 2 ? c0 : c1, a[4 * j + q]) * st[4 * j + 2 * (q & 1) + 1];
      y[q] = PHI ? phi_l(yl) : yl;
    }
    const uint32_t lo = pack2(y[0], y[1]), hi = pack2(y[2], y[3]);
    if ((j + 1) % 2 == 0 && j < 11) { chain(c0, lo, zero); chain(c1, hi, zero); }
    if (j >= 2 && (j & 1) && j < 11) link(c0, tok);
    if (j & 1) {
      if (TRANS) stsm4t(dst + (j - 1) * 1024, plo, phi_, lo, hi);
      else stsm4((j < 8 ? dst : dst2) ^ (((j - 1) & 7) << 4), plo, phi_, lo, hi);
      if (j < 9) tok = token(zaddr);
    }
    plo = lo; phi_ = hi;
  }
}
template <int SLOT>
__device__ __forceinline__ void p2_tile(float (&acc)[40], uint32_t sb, uint32_t wgo, uint32_t par, uint32_t npar, uint32_t eb, int sd, bool& ok) {
  if (!ok) mbar_spin(sb + B_FULL2 + 8 * SLOT, par);
  ok = mbar_test(sb + B_FULL2 + 8 * ((SLOT + 1) % NS2), npar);
  wg_fence();
#pragma unroll
  for (int kk = 0; kk < 4; kk++) wgmma_n80(acc, dlo(p2_off(SLOT)) + wgo + kk * 128, dlo(p2_off(SLOT) + 16384) + kk * 2, kk ? 1 : sd);
  wg_commit();
  wg_wait<1>();
  arrive_elect(eb);
}
__device__ __forceinline__ void epi_ffn(const float (&a)[48], const float (&u)[48], const float (&st)[48], int lane, uint32_t zero,
                                        uint32_t stg_lane) {
  float cg0 = __shfl_sync(0xffffffffu, a[44], lane | 3), cg1 = __shfl_sync(0xffffffffu, a[46], lane | 3);
  const float cu0 = __shfl_sync(0xffffffffu, u[44], lane | 3), cu1 = __shfl_sync(0xffffffffu, u[46], lane | 3);
  uint32_t plo = 0, phi_ = 0;
#pragma unroll
  for (int j = 0; j < 12; j++) {
    float h[4];
#pragma unroll
    for (int q = 0; q < 4; q++) {
      const float nm = st[4 * j + 2 * (q & 1)], rl = st[4 * j + 2 * (q & 1) + 1];
      const float gl = fmaf(nm, q < 2 ? cg0 : cg1, a[4 * j + q]) * rl;
      const float du = fmaf(nm, q < 2 ? cu0 : cu1, u[4 * j + q]);
      h[q] = (gl * du) * (rl * rcp(fmaf(ex2(-gl), LOG2E * LOG2E, LOG2E * LOG2E)));
    }
    const uint32_t lo = pack2(h[0], h[1]), hi = pack2(h[2], h[3]);
    if (j & 1) stsm4t(stg_lane + (j - 1) * 1024, plo, phi_, lo, hi);
    if (j < 11) { chain(cg0, lo, zero); chain(cg1, hi, zero); }
    plo = lo; phi_ = hi;
  }
}

__device__ __forceinline__ void consumer(const Params& p, uint32_t sb, int b, int wg, int tid) {
  int G, rb;
  role1(b, G, rb);
  const int lane = tid & 31, wq = tid >> 5;
  const int mi = lane >> 3, r8 = lane & 7;
  uint32_t stg_lane = sb + SOFF + (8 * (mi >> 1) + r8) * 128 + (((2 * wq + (mi & 1)) ^ r8) << 4);
  asm volatile("mov.u32 %0, %0;" : "+r"(stg_lane));
  const uint32_t zero = p.zero;
  if (wg == 1) ln_stats(sb, tid, G, rb, p.sy);
  {
    float a0[48], a1[48], st[48];
#pragma unroll 1
    for (int s = wg; s < 7; s += 2) {
      float kv[32];
      const uint32_t rot = s > KVS_;
      const uint32_t alA = dlo(WOFF) + rot * (3 * 1024), alB = dlo(WOFF) - rot * (2 * 1024);
      const uint32_t fbA = sb + B_FULL + rot * 24, fbB = sb + B_FULL - rot * 16;
      uint32_t eb = sb + B_DUMMY;
      if (s > 0) bar_sync(1 + wg, 256);
      if (tid == 0) STAMP(3 * s);
      {
        if (s == 0) mbar_spin(sb + B_XFULL, 0);
        mbar_spin(fbA, 0);
        wg_fence();
        wgmma_n96_first(a0, alA, dlo(XOFF));
        wgmma_n96_first(a1, alA + 512, dlo(XOFF));
#pragma unroll
        for (int kk = 1; kk < 4; kk++) {
          wgmma_n96(a0, alA + kk * 128, dlo(XOFF) + kk * 2, 1);
          wgmma_n96(a1, alA + 512 + kk * 128, dlo(XOFF) + kk * 2, 1);
        }
        wg_commit();
        eb = fbA + (B_EMPTY - B_FULL);
      }
#pragma unroll 1
      for (uint32_t h = 0; h < 2; h++) {
        const uint32_t blo = dlo(XOFF) + h * (5 * XCH >> 4);
#pragma unroll
        for (int j = 0; j < 5; j++) {
          const uint32_t alo = (j < 2 ? alA : alB) + j * 1024, fb = (j < 2 ? fbA : fbB) + 8 * j;
          if (j == 0 && h == 0) continue;
          if (s == 0) mbar_spin(sb + B_XFULL + 40 * h + 8 * j, 0);
          mbar_spin(fb, j < 2 ? h : h ^ rot);
          wg_fence();
#pragma unroll
          for (int kk = 0; kk < 4; kk++) {
            wgmma_n96(a0, alo + kk * 128, blo + j * (XCH >> 4) + kk * 2, 1);
            wgmma_n96(a1, alo + 512 + kk * 128, blo + j * (XCH >> 4) + kk * 2, 1);
          }
          wg_commit();
          wg_wait<1>();
          arrive_elect(eb);
          eb = fb + (B_EMPTY - B_FULL);
        }
      }
      if (s == KVS_) {
#pragma unroll
        for (int j = 0; j < 3; j++) {
          mbar_spin(sb + B_FULL + 8 * j, 0);
          wg_fence();
#pragma unroll
          for (int kk = 0; kk < 4; kk++) {
            if (j == 0 && kk == 0) wgmma_n64_kk_first(kv, dlo(WOFF), dlo(WOFF) + 512);
            else wgmma_n64_kk(kv, dlo(WOFF) + j * 1024 + kk * 2, dlo(WOFF) + j * 1024 + 512 + kk * 2, 1);
          }
          wg_commit();
        }
        bar_arrive(2 - wg, 256);
        wg_wait<3>(); arrive_elect(eb);
        wg_wait<2>(); arrive_elect(sb + B_EMPTY);
        wg_wait<1>(); arrive_elect(sb + B_EMPTY + 8);
        eb = sb + B_EMPTY + 16;
      } else if (s < 6) bar_arrive(2 - wg, 256);
      if (s < 2) load_stats(st, sb, lane);
      wg_wait<0>();
      keep(a0); keep(a1);
      arrive_elect(eb);
      if (s == 6) arrive_elect(sb + B_T1);
      if (tid == 0) STAMP(3 * s + 1);
      int ix;
      const int ty = step_info(G, s, ix);
      if (s > 0) mbar_spin(ty == T_KV ? sb + B_S1E : sb + B_STG + 8 * (1 - wg), ((s - 1) >> 1) & 1);
      if (s == KVS_ && b < NKVC) {
        keep(kv);
#pragma unroll
        for (int hf = 0; hf < 2; hf++) {
          const int r = 16 * wq + (lane >> 2) + 8 * hf, hl = r / 20;
          if (hl < 3) {
            const uint32_t dst = sb + SOFF + XCH + 80 * r - 80 * hl + 8 * (lane & 3);
#pragma unroll
            for (int j = 0; j < 8; j++)
              if ((unsigned)(8 * j + 2 * (lane & 3) - 20 * hl) < 20u)
                asm volatile("st.shared.v2.f32 [%0], {%1,%2};" ::"r"(dst + 32 * j), "f"(valid(kv[4 * j + 2 * hf])), "f"(valid(kv[4 * j + 2 * hf + 1])) : "memory");
            if ((lane & 3) == 2) asm volatile("st.shared.f32 [%0], %1;" ::"r"(sb + SOFF + XCH + 4800 + 4 * r), "f"(valid(kv[28 + 2 * hf])) : "memory");
          }
        }
        fence_async_smem();
        mbar_arrive(sb + B_KVF);
      }
      if (ty == T_KV) {
        const uint32_t row = 16 * wq + 8 * (mi & 1) + r8;
        const uint32_t dA = sb + SOFF + row * 128 + (((mi >> 1) ^ r8) << 4), dB = sb + SOFF + 8192 + row * 64 + (((mi >> 1) ^ (r8 >> 1)) << 4);
        epi_attn<false, false>(a1, st, lane, zero, sb + W_ZERO, dA + XCH, dB + XCH);
        fence_async_smem();
        mbar_arrive(sb + B_S1F);
        if (s > 0) mbar_spin(sb + B_STG, 0);
        epi_attn<true, false>(a0, st, lane, zero, sb + W_ZERO, dA, dB);
      } else if (ty == T_QQ) {
        epi_attn<true, true>(a1, st, lane, zero, sb + W_ZERO, stg_lane + XCH, 0);
        fence_async_smem();
        mbar_arrive(sb + B_S1F);
        epi_attn<true, true>(a0, st, lane, zero, sb + W_ZERO, stg_lane, 0);
      } else epi_ffn(a0, a1, st, lane, zero, stg_lane);
      fence_async_smem();
      mbar_arrive(sb + B_STGF + 8 * wg);
      if (tid == 0) STAMP(3 * s + 2);
    }
    if (b >= 130) { arrive_elect(sb + B_FIN); return; }
  }
  int tb, cg;
  role2(b, tb, cg);
  float o[40], sa[40], gt[40];
  const bool do_m = wg == 1 && b < NMC;
  const uint32_t wgo = wg * 512;
  if (tid == 0) STAMP(24 + 4 * wg);
#define P2S(n)
#define EMP(j) (sb + B_EMPTY2 + 8 * (j))
  if (do_m) {
    const int hg = b / 10;
    const float* kvr = p.kvr + ld_rlx(reinterpret_cast<const unsigned*>(p.kvr) + 2 * 12800) * 12800 + hg * 1200;
    uint4 v[3];
    uint32_t all, c = 0;
    do {
#pragma unroll
      for (int w = 0; w < 3; w++) v[w] = ld_rlx128(kvr + 4 * min(tid + 128 * w, hg == 10 ? 199 : 299));
      all = 1;
#pragma unroll
      for (int w = 0; w < 3; w++) all &= v[w].x & v[w].y & v[w].z & v[w].w;
      if (++c > SPIN_LIMIT) TRAP(0);
    } while (!all);
    const uint32_t bt = sb + WOOFF + 8192;
    mbar_spin(sb + B_WO, 0);
#pragma unroll
    for (int q = 0; q < 4; q++) sts128(bt + tid * 16 + q * 2048, make_uint4(0, 0, 0, 0));
    bar_sync(4, 128);
#pragma unroll
    for (int w = 0; w < 3; w++) {
      const int u = min(tid + 128 * w, hg == 10 ? 199 : 299), row = u / 5, off = 40 * (u / 100) + 8 * (u - 5 * row);
      asm volatile("st.shared.v2.u32 [%0], {%1,%2};" ::"r"(bt + row * 128 + (((off >> 4) ^ (row & 7)) << 4) + (off & 8)),
                   "r"(pack2(__uint_as_float(v[w].x) * LN2, __uint_as_float(v[w].y) * LN2)),
                   "r"(pack2(__uint_as_float(v[w].z) * LN2, __uint_as_float(v[w].w) * LN2)) : "memory");
    }
    fence_async_smem();
    bar_sync(4, 128);
    float m[32];
    wg_fence();
#pragma unroll
    for (int kk = 0; kk < 4; kk++) wgmma_n64(m, dlo(WOOFF) + kk * 128, dlo(WOOFF + 8192) + kk * 2, kk);
    wg_commit();
    wg_wait<0>();
    keep(m);
    bar_sync(4, 128);
#pragma unroll
    for (int j = 0; j < 4; j++)
      stsm4t(stg_lane - (SOFF - WOOFF - 8192) + j * 2048, pack2(m[8 * j], m[8 * j + 1]), pack2(m[8 * j + 2], m[8 * j + 3]),
             pack2(m[8 * j + 4], m[8 * j + 5]), pack2(m[8 * j + 6], m[8 * j + 7]));
    fence_async_smem();
    mbar_arrive(sb + B_MF);
  }
  bool ok = false;
#pragma unroll 1
  for (uint32_t r = 0; r < 4; r++) {
    const uint32_t par = r & 1;
    p2_tile<0>(o, sb, wgo, par, par, r == 0 ? sb + B_DUMMY : (r == 1 ? EMP(6) : EMP(7)), r, ok); P2S((r ? 8 * r - 1 : 0))
    p2_tile<1>(o, sb, wgo, par, par, EMP(0), 1, ok); P2S((r ? 8 * r - 1 : 0) + 1)
    p2_tile<2>(o, sb, wgo, par, par, EMP(1), 1, ok); P2S((r ? 8 * r - 1 : 0) + 2)
    p2_tile<3>(o, sb, wgo, par, par, EMP(2), 1, ok); P2S((r ? 8 * r - 1 : 0) + 3)
    if (r == 3) break;
    p2_tile<4>(o, sb, wgo, par, par, EMP(3), 1, ok); P2S((r ? 8 * r - 1 : 0) + 4)
    p2_tile<5>(o, sb, wgo, par, par, EMP(4), 1, ok); P2S((r ? 8 * r - 1 : 0) + 5)
    p2_tile<6>(o, sb, wgo, par, par ^ 1, EMP(5), 1, ok); P2S((r ? 8 * r - 1 : 0) + 6)
    if (r == 0) { ok = false; continue; }
    p2_tile<7>(o, sb, wgo, par ^ 1, par ^ 1, EMP(6), 1, ok); P2S((r ? 8 * r - 1 : 0) + 7)
  }
#define SILU(n)                                                                                    \
  _Pragma("unroll") for (int q = 0; q < 5; q++) {                                                  \
    if ((n) >= 2) gt[5 * ((n) - 2) + q] *= o[5 * ((n) - 2) + q];                                   \
    if ((n) >= 1 && (n) < 9) gt[5 * ((n) - 1) + q] = rcp(1.f + gt[5 * ((n) - 1) + q]);             \
    if ((n) < 8) gt[5 * (n) + q] = ex2(o[5 * (n) + q] * -LOG2E);                                   \
  }
  p2_tile<4>(sa, sb, wgo, 1, 1, EMP(3), 0, ok); keep(o); P2S(27) SILU(0)
  p2_tile<5>(sa, sb, wgo, 1, 1, EMP(4), 1, ok); P2S(28) SILU(1)
  p2_tile<6>(sa, sb, wgo, 1, 0, EMP(5), 1, ok); P2S(29) SILU(2)
  p2_tile<7>(sa, sb, wgo, 0, 0, EMP(6), 1, ok); P2S(30) SILU(3)
  p2_tile<0>(sa, sb, wgo, 0, 0, sb + B_DUMMY, 1, ok); P2S(31) SILU(4)
  p2_tile<1>(sa, sb, wgo, 0, 0, sb + B_DUMMY, 1, ok); P2S(32) SILU(5)
  p2_tile<2>(sa, sb, wgo, 0, 0, sb + B_DUMMY, 1, ok); P2S(33) SILU(6)
  p2_tile<3>(sa, sb, wgo, 0, 0, sb + B_DUMMY, 1, ok); P2S(34) SILU(7)
  p2_tile<4>(sa, sb, wgo, 0, 0, sb + B_DUMMY, 1, ok); P2S(35) SILU(8)
  p2_tile<5>(sa, sb, wgo, 0, 0, sb + B_DUMMY, 1, ok); P2S(36) SILU(9)
  uint32_t xr[20];
  mbar_spin(sb + B_XRES, 0);
  arrive_elect(sb + B_FIN);
  const uint32_t ob = stg_lane - (SOFF - XROFF) + wg * XCH;
#pragma unroll
  for (int j = 0; j < 5; j++) ldsm4t(ob + j * 2048, xr[4 * j], xr[4 * j + 1], xr[4 * j + 2], xr[4 * j + 3]);
  float xf[40];
#pragma unroll
  for (int q = 0; q < 20; q++) { xf[2 * q] = bf_lo(xr[q]); xf[2 * q + 1] = bf_hi(xr[q]); }
  keep(xf); keep(gt);
  wg_wait<0>();
  keep(sa);
  if (tid == 0) STAMP(26 + 4 * wg);
#pragma unroll
  for (int j = 0; j < 5; j++) {
    uint32_t r[4];
#pragma unroll
    for (int q = 0; q < 4; q++) {
      const int e = 8 * j + 2 * q;
      r[q] = pack2(fmaf(sa[e], gt[e], xf[e]), fmaf(sa[e + 1], gt[e + 1], xf[e + 1]));
    }
    stsm4t(ob + j * 2048, r[0], r[1], r[2], r[3]);
  }
  bar_sync(3 + wg, 128);
  {
    const int r0 = tid >> 3, c = tid & 7;
    __nv_bfloat16* dst = p.outp + (size_t)(tb * 80 + r0) * D_ + cg * 128 + wg * 64 + c * 8;
    const uint32_t src = sb + XROFF + wg * XCH + r0 * 128 + ((c ^ (r0 & 7)) << 4);
    uint4 v[5];
#pragma unroll
    for (int i = 0; i < 5; i++) v[i] = lds128(src + i * 2048);
#pragma unroll
    for (int i = 0; i < 5; i++)
      if (tb * 80 + r0 + 16 * i < S_) *reinterpret_cast<uint4*>(dst + 16 * i * D_) = v[i];
  }
  if (tid == 0) STAMP(27 + 4 * wg);
}

__global__ void __launch_bounds__(384, 1) fused_kernel(const __grid_constant__ Params p) {
  extern __shared__ __align__(1024) unsigned char smem[];
  uint32_t sb = (uint32_t)__cvta_generic_to_shared(smem);
  asm volatile("mov.u32 %0, %0;" : "+r"(sb));
  const int b = blockIdx.x;
  const int warp = __shfl_sync(0xffffffffu, threadIdx.x >> 5, 0), lane = threadIdx.x & 31;
  if (warp >= 8) {
    asm volatile("setmaxnreg.dec.sync.aligned.u32 88;");
    if (warp == 8) producer(p, sb, b, lane);
    else {
      if (elect_one()) {
#pragma unroll
        for (int w = 0; w < 3; w++) {
          if (warp == 9 + w) {
#pragma unroll
            for (int i = I_EMPTY + 13 * w; i < min(I_EMPTY + 13 * w + 13, (int)I_S7); i++)
              mbar_init(sb + MOFF + 8 * i, (i < I_FULL2 || i == I_T1) ? 4 : (i >= I_EMPTY2 && i < I_STATS) ? 8 : i == I_STATS ? 32 :
                                           i == I_DUMMY ? 100000 : i == I_FIN ? 9 : ((i >= I_STGF && i <= I_MF) || i == I_S1F) ? 128 : 1);
          }
        }
        if (warp == 11) {
          mbar_init(sb + B_S7, 1);
          sts64v(sb + W_READY, 0); sts64v(sb + W_ZERO - 4, 0);
          if ((sb & 0x3FFFF) != 1024) TRAP(0);
        }
        fence_async_smem();
      }
      __syncwarp();
      bar_arrive(7, 128);
      bar_sync(0, 384);
      if (warp == 9) agent(p, sb, b, lane);
      else aux(p, sb, b, warp - 10, lane);
    }
  } else {
    if (threadIdx.x < 160) {
      const int i = threadIdx.x;
      sts128(sb + XOFF + (i >> 4) * XCH + TB * 128 + (i & 15) * 16, make_uint4(0x3F803F80u, 0x3F803F80u, 0x3F803F80u, 0x3F803F80u));
      fence_async_smem();
    }
    __syncwarp();
    asm volatile("setmaxnreg.inc.sync.aligned.u32 208;");
    bar_sync(0, 384);
    consumer(p, sb, b, warp >> 2, threadIdx.x & 127);
  }
}

__device__ float g_fb[S_ * (D_ + 3 * D_ + 2 * F_ + 2 * D_) + 32 * 420];
__global__ void fb_ln(const __nv_bfloat16* x, float* xn) {
  const int r = blockIdx.x, l = threadIdx.x;
  float v[20], s = 0.f, q = 0.f;
  for (int i = 0; i < 20; i++) { v[i] = __bfloat162float(x[r * D_ + l + 32 * i]); s += v[i]; }
  for (int o = 16; o; o >>= 1) s += __shfl_xor_sync(0xffffffffu, s, o);
  for (int i = 0; i < 20; i++) { v[i] -= s * (1.f / D_); q += v[i] * v[i]; }
  for (int o = 16; o; o >>= 1) q += __shfl_xor_sync(0xffffffffu, q, o);
  for (int i = 0; i < 20; i++) xn[r * D_ + l + 32 * i] = v[i] * rsqrtf(q * (1.f / D_) + 1e-5f);
}
__global__ void fb_gemm(const float* A, const __nv_bfloat16* W, float* C, int N, int K) {
  const int n = blockIdx.x * 128 + threadIdx.x, m = blockIdx.y * 8;
  if (n >= N) return;
  float c[8] = {0.f, 0.f, 0.f, 0.f, 0.f, 0.f, 0.f, 0.f};
  for (int k = 0; k < K; k++) {
    const float w = __bfloat162float(W[k * N + n]);
    for (int i = 0; i < 8; i++) c[i] = fmaf(A[(m + i) * K + k], w, c[i]);
  }
  for (int i = 0; i < 8; i++) C[(m + i) * N + n] = c[i];
}
__device__ float fb_phi(float t) { return (t > 0.f ? t + 1.f : expf(t)) + 1e-6f; }
__global__ void fb_kv(const float* qkv, float* kv) {
  const int h = blockIdx.x, d = threadIdx.x / 21, e = threadIdx.x % 21;
  float s = 0.f;
  for (int t = 0; t < S_; t++) s += fb_phi(qkv[t * 3 * D_ + D_ + 20 * h + d]) * (e < 20 ? qkv[t * 3 * D_ + 2 * D_ + 20 * h + e] : 1.f);
  kv[h * 420 + threadIdx.x] = s;
}
__global__ void fb_mid(const float* qkv, const float* kv, float* o, float* g, const float* u) {
  const int t = blockIdx.x, c = threadIdx.x, h = c / 20;
  float num = 0.f, den = 1e-6f;
  for (int d = 0; d < 20; d++) {
    const float pq = fb_phi(qkv[t * 3 * D_ + 20 * h + d]);
    num += pq * kv[h * 420 + d * 21 + c % 20]; den += pq * kv[h * 420 + d * 21 + 20];
  }
  o[t * D_ + c] = num / den;
  for (int f = c; f < F_; f += D_) g[t * F_ + f] = g[t * F_ + f] / (1.f + expf(-g[t * F_ + f])) * u[t * F_ + f];
}
__global__ void fb_out(const __nv_bfloat16* x, const float* s, const float* g, __nv_bfloat16* y) {
  const int i = blockIdx.x * D_ + threadIdx.x;
  y[i] = __float2bfloat16(__bfloat162float(x[i]) + s[i] * (g[i] / (1.f + expf(-g[i]))));
}
void fallback(void* const* d_in, void* d_out, float* base) {
  typedef const __nv_bfloat16* P;
  float *xn = base, *qkv = xn + S_ * D_, *g = qkv + S_ * 3 * D_, *u = g + S_ * F_, *s = u + S_ * F_, *go = s + S_ * D_, *kv = go + S_ * D_;
  fb_ln<<<S_, 32>>>((P)d_in[0], xn);
  fb_gemm<<<dim3(15, S_ / 8), 128>>>(xn, (P)d_in[1], qkv, 3 * D_, D_);
  fb_gemm<<<dim3(14, S_ / 8), 128>>>(xn, (P)d_in[4], g, F_, D_);
  fb_gemm<<<dim3(14, S_ / 8), 128>>>(xn, (P)d_in[5], u, F_, D_);
  fb_kv<<<32, 420>>>(qkv, kv);
  fb_mid<<<S_, D_>>>(qkv, kv, xn, g, u);
  fb_gemm<<<dim3(5, S_ / 8), 128>>>(xn, (P)d_in[2], s, D_, D_);
  fb_gemm<<<dim3(5, S_ / 8), 128>>>(g, (P)d_in[6], go, D_, F_);
  fb_out<<<S_, D_>>>((P)d_in[0], s, go, (__nv_bfloat16*)d_out);
}

typedef CUresult (*EncodeFn)(CUtensorMap*, CUtensorMapDataType, cuuint32_t, void*, const cuuint64_t*, const cuuint64_t*,
                             const cuuint32_t*, const cuuint32_t*, CUtensorMapInterleave, CUtensorMapSwizzle,
                             CUtensorMapL2promotion, CUtensorMapFloatOOBfill);

void make_map(EncodeFn enc, CUtensorMap* m, const void* ptr, uint64_t rows, uint64_t cols, uint32_t box_rows, uint32_t box_cols = 64) {
  cuuint64_t gd[2] = {cols, rows}, gs[1] = {cols * 2};
  cuuint32_t bd[2] = {box_cols, box_rows}, es[2] = {1, 1};
  CUresult r = enc(m, CU_TENSOR_MAP_DATA_TYPE_BFLOAT16, 2, const_cast<void*>(ptr), gd, gs, bd, es, CU_TENSOR_MAP_INTERLEAVE_NONE,
                   box_cols == 64 ? CU_TENSOR_MAP_SWIZZLE_128B : CU_TENSOR_MAP_SWIZZLE_64B, CU_TENSOR_MAP_L2_PROMOTION_L2_128B, CU_TENSOR_MAP_FLOAT_OOB_FILL_NONE);
  if (r != CUDA_SUCCESS) fprintf(stderr, "cuTensorMapEncodeTiled failed: %d\n", (int)r);
}

void make_map3(EncodeFn enc, CUtensorMap* m, const void* ptr, uint64_t rows) {
  cuuint64_t gd[3] = {64, rows, 10}, gs[2] = {D_ * 2, 128};
  cuuint32_t bd[3] = {64, 64, 2}, es[3] = {1, 1, 1};
  CUresult r = enc(m, CU_TENSOR_MAP_DATA_TYPE_BFLOAT16, 3, const_cast<void*>(ptr), gd, gs, bd, es, CU_TENSOR_MAP_INTERLEAVE_NONE,
                   CU_TENSOR_MAP_SWIZZLE_128B, CU_TENSOR_MAP_L2_PROMOTION_L2_128B, CU_TENSOR_MAP_FLOAT_OOB_FILL_NONE);
  if (r != CUDA_SUCCESS) fprintf(stderr, "cuTensorMapEncodeTiled failed: %d\n", (int)r);
}

}

extern "C" void kernel_launch(void* const* d_in, const int* in_sizes, int n_in, void* d_out, int out_size) {
  (void)in_sizes; (void)n_in; (void)out_size;
  static bool ready = false, fused = false;
  static EncodeFn enc = nullptr;
  static void *pH, *pPQ, *pM, *pKV, *pKvp, *pZp, *pSy, *pMask, *pKvr, *pFb;
  if (!ready) {
    ready = true;
    void* fn = nullptr;
    cudaDriverEntryPointQueryResult st;
    cudaGetDriverEntryPoint("cuTensorMapEncodeTiled", &fn, cudaEnableDefault, &st);
    enc = (EncodeFn)fn;
    cudaGetSymbolAddress(&pH, g_H); cudaGetSymbolAddress(&pPQ, g_PQ); cudaGetSymbolAddress(&pM, g_M); cudaGetSymbolAddress(&pKV, g_KVT);
    cudaGetSymbolAddress(&pKvp, g_kvp); cudaGetSymbolAddress(&pZp, g_zp); cudaGetSymbolAddress(&pSy, g_sync);
    cudaGetSymbolAddress(&pMask, g_mask); cudaGetSymbolAddress(&pKvr, g_kvr); cudaGetSymbolAddress(&pFb, g_fb);
    int dev = 0, sms = 0, occ = 0;
    cudaGetDevice(&dev);
    cudaDeviceGetAttribute(&sms, cudaDevAttrMultiProcessorCount, dev);
    if (cudaFuncSetAttribute(fused_kernel, cudaFuncAttributeMaxDynamicSharedMemorySize, SMEM_BYTES) == cudaSuccess)
      cudaOccupancyMaxActiveBlocksPerMultiprocessor(&occ, fused_kernel, 384, SMEM_BYTES);
    fused = enc != nullptr && sms * occ >= NCTA;
    (void)cudaGetLastError();
  }
  if (!fused) { fallback(d_in, d_out, (float*)pFb); return; }
  Params p;
  const void *x = d_in[0], *wqkv = d_in[1], *wo = d_in[2], *w1 = d_in[4], *w3 = d_in[5], *w2 = d_in[6];
  make_map(enc, &p.x1, x, S_, D_, TB);
  make_map(enc, &p.wqkv, wqkv, D_, 3 * D_, 64);
  make_map(enc, &p.w1, w1, D_, F_, 64);
  make_map(enc, &p.w3, w3, D_, F_, 64);
  make_map(enc, &p.hst, pH, S_, F_, TB);
  make_map(enc, &p.pqst, pPQ, S_, D_, TB);
  make_map3(enc, &p.w2, w2, F_);
  make_map3(enc, &p.mm, pM, D_);
  make_map(enc, &p.hld, pH, S_, F_, 80);
  make_map(enc, &p.ald, pPQ, S_, D_, 80);
  make_map(enc, &p.xres, x, S_, D_, 80);
  make_map(enc, &p.kva, pKV, 2 * D_, KTP, 64);
  make_map(enc, &p.kvb, pKV, 2 * D_, KTP, 64, 32);
  make_map(enc, &p.vld, pKV, 2 * D_, KTP, 60);
  make_map(enc, &p.msk, pMask, 4, KTP, 4);
  make_map(enc, &p.wom, wo, D_, D_, 64);
  make_map(enc, &p.mst, pM, D_, D_, 60);
  p.outp = (__nv_bfloat16*)d_out;
  p.wo = (const __nv_bfloat16*)wo;
  p.w2p = (const __nv_bfloat16*)w2;
  p.mask_p = (__nv_bfloat16*)pMask; p.kvr = (float*)pKvr; p.pq_p = (__nv_bfloat16*)pPQ;
  p.zero = 0;
  p.kvp = (float*)pKvp; p.zp = (float*)pZp; p.sy = (Sync*)pSy;
  fused_kernel<<<NCTA, 384, SMEM_BYTES>>>(p);
}
```
